```python
import torch

def _softmax(x, axis=-1):
    return torch.softmax(x, dim=axis)
def _gelu(x):
    return torch.nn.functional.gelu(x, approximate="tanh")
def _silu(x):
    return torch.nn.functional.silu(x)
def _sigmoid(x):
    return torch.sigmoid(x)
def _layernorm(x, axis=-1, eps=1e-5):
    m = x.mean(dim=axis, keepdim=True)
    v = x.var(dim=axis, keepdim=True, unbiased=False)
    return (x - m) / torch.sqrt(v + eps)
def _scatter_add(tgt, idx, src, axis=0):
    return tgt.clone().index_add_(axis, idx, src)
def _segment_sum(src, seg, n):
    out = torch.zeros((n,) + src.shape[1:], dtype=src.dtype)
    return out.index_add_(0, seg, src)
def _pad(x, pw):
    flat = tuple(v for pair in reversed(pw) for v in pair)
    return torch.nn.functional.pad(x, flat)

kernel_name = 'standalone__gqa_softmax__near_ridge'

def setup_inputs():

    _w = (lambda a: (lambda t: t.to(torch.bfloat16) if t.is_floating_point() else t)(torch.as_tensor(a)))
    B, Hq, Hkv, Sq, Sk, D = 16, 32, 32, 848, 512, 192
    return {
        "q": _w((lambda *s: torch.randn(*s, dtype=torch.bfloat16) * 0.8)(B, Hq, Sq, D)),
        "k": _w((lambda *s: torch.randn(*s, dtype=torch.bfloat16) * 0.8)(B, Hkv, Sk, D)),
        "v": _w((lambda *s: torch.randn(*s, dtype=torch.bfloat16) * 0.05)(B, Hkv, Sk, D)),
    }

def reference(q, k, v):
    B, Hq, Sq, D = q.shape
    Hkv = k.shape[1]
    rep = Hq // Hkv
    k = (lambda x, n, axis: torch.repeat_interleave(x, n, dim=axis))(k, rep, axis=1)
    v = (lambda x, n, axis: torch.repeat_interleave(x, n, dim=axis))(v, rep, axis=1)
    scale = D ** -0.5
    scores = torch.einsum("bhqd,bhkd->bhqk", q, k) * scale
    p = _softmax(scores, axis=-1)
    return torch.einsum("bhqk,bhkd->bhqd", p, v)
```

```cpp
#include <cuda_runtime.h>
#include <cuda_bf16.h>
#include <cuda.h>
#include <stdint.h>

namespace {

constexpr int NHEADS = 512;
constexpr int SQ = 848;
constexpr int SK = 512;
constexpr int DH = 192;
constexpr int ROW_BYTES = DH * 2;
constexpr int NBLK = SK / 64;
constexpr int NUM_CLUSTERS = 66;

#define MINI 1
#define PRESCALE 1

constexpr uint32_t GRP_BYTES = 3072, SLAB_BYTES = 1024;
constexpr uint32_t BLK_BYTES = 64 * ROW_BYTES;
constexpr uint32_t REM_BYTES = 16 * ROW_BYTES;
constexpr uint32_t SM_BAR = 0;
constexpr uint32_t SM_REM = 1024;
constexpr uint32_t SM_V = SM_REM + REM_BYTES;
constexpr uint32_t SM_K = SM_V + 3 * BLK_BYTES;
constexpr uint32_t SM_QO = SM_K + 4 * BLK_BYTES;
constexpr uint32_t SM_PT = SM_QO + 2 * BLK_BYTES;
constexpr uint32_t SMEM_BYTES = SM_PT + 2 * 2048;
#define T_KVPF 4
#define KROT 2
constexpr uint32_t BAR_FULL = SM_BAR;
constexpr uint32_t BAR_DONE = BAR_FULL + 32;
constexpr uint32_t BAR_QFULL = BAR_DONE + 32;
constexpr uint32_t BAR_OREADY = BAR_QFULL + 16;
constexpr uint32_t BAR_STORED = BAR_OREADY + 16;
constexpr uint32_t BAR_DUMMY = BAR_STORED + 16;
constexpr uint32_t SM_REDO = BAR_DUMMY + 8;
constexpr uint32_t SM_LSUM = SM_BAR + 256;
static_assert(SMEM_BYTES <= 232448, "smem");

constexpr int PRODUCER_REGS = 24, CONSUMER_REGS = 240;
#define STAGE_SPLIT 4
#define STG_CVTK 3
#define VW_EARLY 0
#define PUB_B 1
#define GAPW 3
#define DUPI 1
#define NPRE7 32
#define QS_POS 32
constexpr float SCALE_LOG2E = 0.07216878364870323f * 1.4426950408889634f;
constexpr uint32_t SCALE_HI = 0x3DD53DD5u, SCALE_LO = 0x38EE38EEu;
constexpr uint32_t SUM_LOW = (127u - 14u) << 23, SUM_HIGH = (127u + 32u) << 23;

constexpr int EARLY_CLUSTERS = 10, START_STEP = 60;
constexpr int SCHED_COUNT = 29, SCHED_SHORT = 30;
__constant__ __align__(64) uint16_t SCHED[NUM_CLUSTERS][32] = {
    {0, 3, 150, 228, 299, 377, 451, 529, 605, 681, 757, 811, 909, 955, 1057, 1091, 1206, 1282, 1331, 1429, 1509, 1563, 1646, 1729, 1779, 1861, 1942, 2021, 0, 28, 43090, 292},
    {1, 88, 155, 229, 305, 382, 458, 531, 608, 667, 758, 836, 891, 986, 1051, 1138, 1213, 1289, 1365, 1427, 1514, 1579, 1662, 1742, 1803, 1884, 1923, 2022, 0, 28, 21124, 1320},
    {2, 11, 152, 219, 302, 378, 453, 530, 609, 675, 760, 837, 899, 988, 1059, 1140, 1203, 1284, 1362, 1440, 1516, 1592, 1668, 1731, 1818, 1891, 1966, 2019, 0, 28, 21002, 2689},
    {4, 19, 153, 230, 306, 384, 460, 539, 610, 686, 755, 838, 914, 979, 1062, 1123, 1214, 1283, 1364, 1441, 1517, 1593, 1667, 1744, 1811, 1885, 1968, 2027, 0, 28, 42114, 2370},
    {5, 27, 154, 232, 308, 385, 461, 536, 613, 691, 764, 835, 916, 987, 1064, 1141, 1211, 1290, 1363, 1442, 1507, 1588, 1664, 1715, 1806, 1886, 1931, 2024, 0, 28, 10754, 1173},
    {6, 35, 156, 233, 309, 386, 459, 532, 612, 683, 761, 819, 910, 963, 1058, 1099, 1208, 1285, 1339, 1430, 1510, 1571, 1648, 1730, 1808, 1888, 1939, 2025, 0, 28, 43586, 1060},
    {8, 43, 157, 234, 310, 379, 454, 533, 595, 682, 739, 833, 883, 985, 1060, 1107, 1209, 1286, 1347, 1432, 1475, 1568, 1619, 1702, 1781, 1862, 1944, 2026, 0, 28, 38178, 84},
    {9, 89, 161, 237, 313, 387, 462, 537, 614, 688, 763, 840, 907, 990, 1066, 1139, 1217, 1291, 1366, 1444, 1515, 1594, 1669, 1739, 1820, 1899, 1969, 2035, 0, 28, 37920, 2706},
    {10, 51, 158, 236, 307, 380, 456, 523, 606, 684, 747, 834, 912, 971, 1061, 1115, 1210, 1275, 1353, 1433, 1483, 1569, 1649, 1732, 1787, 1864, 1945, 2028, 0, 28, 42130, 274},
    {12, 59, 160, 227, 304, 381, 457, 534, 603, 685, 762, 827, 913, 989, 1065, 1131, 1216, 1292, 1368, 1435, 1518, 1587, 1665, 1723, 1809, 1867, 1946, 2029, 0, 28, 35082, 680},
    {13, 90, 166, 244, 321, 398, 478, 556, 636, 713, 790, 873, 952, 1029, 1109, 1184, 1262, 1342, 1420, 1500, 1555, 1630, 1713, 1792, 1876, 1958, 2046, 0, 0, 27, 0, 16},
    {14, 67, 162, 238, 314, 390, 468, 542, 620, 694, 772, 849, 925, 1002, 1081, 1157, 1236, 1314, 1393, 1473, 1523, 1596, 1672, 1748, 1822, 1898, 1974, 0, 0, 27, 2, 16},
    {16, 92, 163, 240, 315, 388, 464, 538, 616, 689, 765, 841, 917, 993, 1069, 1144, 1220, 1294, 1370, 1446, 1521, 1598, 1676, 1752, 1826, 1902, 1978, 0, 0, 27, 20, 0},
    {17, 93, 168, 248, 325, 401, 481, 547, 622, 698, 776, 853, 928, 1005, 1084, 1160, 1238, 1317, 1397, 1477, 1554, 1633, 1716, 1794, 1835, 1906, 1982, 0, 0, 27, 128, 256},
    {18, 94, 170, 250, 328, 404, 484, 561, 640, 720, 796, 878, 931, 1008, 1086, 1162, 1241, 1321, 1401, 1481, 1531, 1601, 1680, 1758, 1833, 1910, 1986, 0, 0, 27, 4096, 16},
    {20, 75, 164, 235, 312, 389, 465, 540, 617, 690, 766, 842, 918, 994, 1070, 1145, 1221, 1296, 1373, 1449, 1525, 1604, 1682, 1761, 1837, 1914, 1990, 0, 0, 27, 10, 0},
    {21, 96, 172, 252, 330, 408, 488, 565, 644, 724, 800, 843, 932, 1012, 1090, 1166, 1246, 1325, 1405, 1485, 1539, 1606, 1685, 1764, 1841, 1918, 1994, 0, 0, 27, 2048, 16},
    {22, 97, 173, 253, 332, 409, 489, 566, 627, 701, 778, 858, 933, 1013, 1092, 1168, 1248, 1307, 1376, 1452, 1528, 1608, 1686, 1765, 1842, 1921, 1997, 0, 0, 27, 256, 2},
    {24, 98, 171, 241, 316, 395, 466, 541, 618, 692, 768, 844, 920, 997, 1073, 1148, 1224, 1298, 1377, 1453, 1529, 1609, 1688, 1766, 1846, 1925, 2001, 0, 0, 27, 36, 0},
    {25, 100, 174, 254, 333, 412, 492, 555, 625, 702, 780, 860, 936, 1016, 1094, 1170, 1252, 1329, 1409, 1489, 1565, 1644, 1726, 1800, 1878, 1962, 1995, 0, 0, 27, 128, 1024},
    {26, 101, 176, 256, 334, 413, 494, 572, 649, 729, 806, 886, 962, 1041, 1121, 1193, 1272, 1323, 1410, 1451, 1530, 1610, 1689, 1768, 1848, 1929, 2005, 0, 0, 27, 0, 10},
    {28, 83, 165, 242, 317, 392, 470, 546, 626, 704, 781, 861, 938, 1018, 1097, 1173, 1253, 1330, 1412, 1490, 1547, 1613, 1692, 1770, 1850, 1932, 2009, 0, 0, 27, 2, 16},
    {29, 102, 178, 260, 338, 416, 497, 574, 652, 732, 795, 864, 941, 1020, 1098, 1174, 1254, 1332, 1371, 1457, 1534, 1616, 1694, 1773, 1853, 1934, 2013, 0, 0, 27, 1024, 4},
    {30, 104, 181, 262, 340, 417, 498, 576, 653, 734, 810, 888, 964, 1011, 1100, 1176, 1227, 1305, 1384, 1461, 1538, 1620, 1698, 1777, 1857, 1938, 2017, 0, 0, 27, 8192, 1},
    {32, 105, 184, 264, 331, 396, 476, 552, 630, 708, 785, 866, 945, 1024, 1104, 1180, 1257, 1334, 1413, 1492, 1566, 1645, 1728, 1805, 1882, 1965, 2011, 0, 0, 27, 16, 1024},
    {33, 106, 185, 265, 341, 420, 501, 578, 657, 738, 814, 892, 969, 1045, 1124, 1179, 1260, 1338, 1416, 1494, 1572, 1627, 1705, 1784, 1866, 1949, 2033, 0, 0, 27, 32768, 32},
    {34, 108, 186, 266, 344, 422, 504, 563, 632, 709, 786, 869, 948, 1003, 1077, 1153, 1229, 1308, 1386, 1466, 1544, 1625, 1708, 1786, 1869, 1952, 2037, 0, 0, 27, 8320, 0},
    {36, 109, 188, 251, 320, 397, 477, 554, 634, 710, 788, 870, 949, 1026, 1106, 1147, 1232, 1310, 1389, 1469, 1546, 1628, 1710, 1789, 1872, 1954, 2041, 0, 0, 27, 32776, 0},
    {37, 110, 189, 269, 346, 425, 505, 582, 635, 712, 789, 872, 950, 1028, 1108, 1155, 1233, 1312, 1390, 1470, 1548, 1629, 1712, 1790, 1873, 1956, 2044, 0, 0, 27, 33024, 0},
    {38, 112, 179, 245, 322, 400, 480, 557, 637, 714, 771, 848, 924, 1001, 1080, 1156, 1234, 1313, 1392, 1472, 1549, 1595, 1670, 1746, 1821, 1896, 1972, 0, 0, 27, 1028, 32},
    {40, 113, 187, 246, 324, 403, 469, 544, 621, 696, 773, 850, 915, 992, 1068, 1142, 1218, 1293, 1369, 1445, 1520, 1597, 1673, 1749, 1824, 1900, 1976, 0, 0, 27, 4132, 0},
    {41, 114, 190, 270, 349, 428, 506, 584, 643, 716, 792, 874, 953, 1030, 1110, 1185, 1265, 1345, 1395, 1476, 1553, 1611, 1677, 1753, 1828, 1904, 1980, 0, 0, 27, 256, 36},
    {42, 91, 169, 249, 326, 402, 482, 560, 638, 717, 794, 877, 956, 1033, 1113, 1188, 1243, 1318, 1398, 1478, 1556, 1634, 1675, 1756, 1830, 1908, 1984, 0, 0, 27, 2, 65},
    {44, 116, 192, 272, 350, 429, 508, 586, 662, 715, 797, 880, 939, 1009, 1088, 1164, 1242, 1299, 1372, 1448, 1524, 1602, 1681, 1760, 1834, 1912, 1988, 0, 0, 27, 4608, 2},
    {45, 117, 194, 259, 329, 405, 467, 545, 624, 700, 777, 856, 930, 1010, 1089, 1165, 1245, 1324, 1404, 1484, 1560, 1638, 1718, 1755, 1838, 1916, 1992, 0, 0, 27, 72, 128},
    {46, 118, 196, 276, 353, 430, 509, 588, 664, 742, 818, 896, 947, 1036, 1116, 1189, 1268, 1346, 1422, 1467, 1561, 1640, 1720, 1796, 1843, 1920, 1996, 0, 0, 27, 4096, 264},
    {48, 120, 198, 278, 347, 410, 490, 568, 645, 725, 801, 882, 958, 1037, 1117, 1171, 1249, 1326, 1406, 1486, 1562, 1641, 1722, 1763, 1844, 1922, 1998, 0, 0, 27, 32784, 128},
    {49, 121, 200, 280, 356, 434, 491, 569, 646, 726, 802, 851, 934, 1014, 1093, 1169, 1250, 1328, 1408, 1488, 1564, 1642, 1725, 1798, 1851, 1926, 2002, 0, 0, 27, 2112, 256},
    {50, 122, 201, 281, 357, 436, 514, 593, 669, 723, 804, 884, 960, 1038, 1118, 1190, 1269, 1349, 1425, 1504, 1582, 1657, 1741, 1817, 1883, 1964, 2003, 0, 0, 27, 512, 1280},
    {52, 99, 177, 257, 336, 414, 496, 573, 650, 730, 808, 859, 937, 1017, 1096, 1172, 1219, 1300, 1378, 1454, 1532, 1612, 1690, 1769, 1849, 1930, 2006, 0, 0, 27, 2050, 1},
    {53, 124, 195, 258, 337, 411, 472, 548, 628, 705, 782, 862, 940, 995, 1074, 1149, 1225, 1301, 1380, 1456, 1533, 1614, 1693, 1772, 1852, 1933, 2010, 0, 0, 27, 8228, 0},
    {54, 107, 180, 261, 323, 393, 473, 549, 611, 693, 769, 845, 921, 998, 1076, 1150, 1226, 1302, 1381, 1458, 1536, 1617, 1696, 1774, 1854, 1936, 2014, 0, 0, 27, 274, 0},
    {56, 115, 182, 243, 318, 394, 474, 550, 629, 706, 784, 865, 944, 1022, 1101, 1177, 1235, 1306, 1385, 1462, 1540, 1621, 1700, 1778, 1858, 1940, 2018, 0, 0, 27, 10, 1},
    {57, 125, 204, 284, 355, 418, 500, 577, 656, 737, 813, 890, 966, 1042, 1075, 1181, 1258, 1336, 1414, 1493, 1570, 1650, 1733, 1810, 1889, 1947, 2030, 0, 0, 27, 16400, 512},
    {58, 126, 205, 267, 342, 421, 502, 580, 658, 740, 803, 868, 946, 1025, 1105, 1182, 1261, 1340, 1417, 1496, 1573, 1635, 1706, 1785, 1868, 1950, 2034, 0, 0, 27, 1032, 32},
    {60, 128, 203, 268, 345, 424, 475, 553, 633, 699, 770, 846, 922, 1000, 1078, 1154, 1230, 1309, 1388, 1468, 1545, 1626, 1709, 1788, 1870, 1953, 2038, 0, 0, 27, 580, 0},
    {61, 129, 206, 285, 362, 441, 499, 581, 660, 741, 817, 894, 972, 1048, 1126, 1198, 1277, 1357, 1403, 1497, 1576, 1653, 1736, 1813, 1893, 1971, 2042, 0, 0, 27, 64, 516},
    {62, 130, 209, 288, 365, 444, 522, 601, 677, 753, 829, 905, 981, 1056, 1137, 1212, 1288, 1355, 1437, 1513, 1590, 1659, 1738, 1795, 1874, 1957, 2045, 0, 0, 27, 0, 162},
    {64, 132, 210, 289, 366, 445, 524, 602, 678, 754, 830, 906, 982, 1035, 1129, 1187, 1264, 1344, 1421, 1459, 1550, 1632, 1714, 1793, 1827, 1897, 1973, 0, 0, 27, 40960, 264},
    {65, 133, 212, 275, 348, 426, 483, 558, 619, 697, 774, 852, 926, 1004, 1082, 1158, 1237, 1316, 1394, 1474, 1552, 1603, 1674, 1750, 1825, 1901, 1977, 0, 0, 27, 328, 32},
    {66, 134, 213, 290, 368, 446, 525, 579, 661, 707, 793, 876, 954, 1032, 1112, 1186, 1266, 1315, 1396, 1443, 1522, 1600, 1678, 1754, 1829, 1905, 1981, 0, 0, 27, 640, 10},
    {68, 136, 214, 292, 369, 448, 507, 585, 651, 718, 779, 854, 929, 1006, 1085, 1161, 1240, 1320, 1400, 1480, 1557, 1636, 1683, 1757, 1832, 1909, 1985, 0, 0, 27, 1344, 64},
    {69, 123, 193, 273, 352, 419, 485, 562, 641, 721, 798, 881, 957, 1034, 1114, 1163, 1244, 1322, 1402, 1482, 1558, 1637, 1717, 1747, 1836, 1913, 1989, 0, 0, 27, 32802, 128},
    {70, 137, 211, 274, 339, 406, 486, 564, 642, 722, 787, 857, 923, 996, 1072, 1146, 1222, 1297, 1374, 1450, 1526, 1605, 1684, 1762, 1840, 1917, 1993, 0, 0, 27, 5140, 0},
    {72, 131, 197, 277, 354, 432, 510, 589, 665, 744, 820, 897, 973, 1049, 1130, 1201, 1278, 1358, 1438, 1499, 1578, 1643, 1721, 1797, 1877, 1960, 1979, 0, 0, 27, 2, 1064},
    {73, 138, 216, 293, 363, 433, 512, 590, 666, 745, 821, 898, 974, 1050, 1132, 1202, 1280, 1360, 1411, 1501, 1580, 1651, 1724, 1771, 1845, 1924, 2000, 0, 0, 27, 16, 164},
    {74, 140, 217, 294, 370, 435, 513, 592, 668, 746, 822, 900, 976, 1052, 1133, 1204, 1267, 1348, 1424, 1502, 1581, 1656, 1740, 1816, 1875, 1961, 1987, 0, 0, 27, 32, 1281},
    {76, 141, 218, 283, 358, 427, 493, 570, 648, 728, 805, 885, 961, 1040, 1120, 1192, 1270, 1350, 1426, 1505, 1584, 1658, 1691, 1801, 1859, 1928, 2004, 0, 0, 27, 40, 320},
    {77, 142, 220, 296, 372, 449, 526, 604, 680, 756, 832, 908, 984, 1043, 1134, 1205, 1281, 1361, 1419, 1506, 1585, 1660, 1699, 1802, 1880, 1907, 2008, 0, 0, 27, 8192, 580},
    {78, 144, 221, 291, 360, 437, 516, 594, 670, 748, 824, 901, 977, 1053, 1083, 1194, 1273, 1352, 1428, 1508, 1586, 1661, 1707, 1804, 1881, 1915, 2012, 0, 0, 27, 16392, 576},
    {80, 139, 202, 282, 361, 438, 517, 596, 659, 733, 809, 867, 942, 1021, 1067, 1152, 1228, 1304, 1382, 1460, 1537, 1618, 1697, 1776, 1856, 1937, 2016, 0, 0, 27, 18690, 0},
    {81, 145, 222, 297, 371, 440, 518, 571, 654, 736, 812, 889, 965, 1019, 1102, 1178, 1256, 1333, 1379, 1464, 1541, 1622, 1701, 1780, 1860, 1941, 2020, 0, 0, 27, 8336, 4},
    {82, 146, 224, 298, 373, 450, 528, 587, 672, 749, 825, 875, 968, 1044, 1122, 1196, 1251, 1337, 1387, 1465, 1542, 1624, 1704, 1782, 1865, 1948, 2032, 0, 0, 27, 2176, 5},
    {84, 148, 225, 300, 374, 443, 520, 597, 673, 731, 816, 893, 970, 1046, 1125, 1197, 1274, 1354, 1434, 1512, 1589, 1666, 1745, 1819, 1890, 1955, 2036, 0, 0, 27, 544, 640},
    {85, 149, 226, 301, 376, 452, 515, 598, 674, 750, 826, 902, 978, 1054, 1136, 1195, 1276, 1356, 1436, 1491, 1574, 1652, 1734, 1812, 1892, 1963, 2040, 0, 0, 27, 32832, 520},
    {86, 147, 208, 286, 364, 442, 521, 600, 676, 752, 828, 904, 980, 1027, 1128, 1200, 1259, 1341, 1418, 1498, 1577, 1654, 1737, 1814, 1894, 1970, 2043, 0, 0, 27, 8194, 1025},
};

__device__ __forceinline__ uint32_t smem_u32(const void* p) { return (uint32_t)__cvta_generic_to_shared(p); }
__device__ __forceinline__ void mbar_init(uint32_t bar, uint32_t cnt) {
    asm volatile("mbarrier.init.shared::cta.b64 [%0], %1;" ::"r"(bar), "r"(cnt));
}
__device__ __forceinline__ void mbar_expect_tx(uint32_t bar, uint32_t bytes) {
    asm volatile("mbarrier.arrive.expect_tx.shared::cta.b64 _, [%0], %1;" ::"r"(bar), "r"(bytes) : "memory");
}
__device__ __forceinline__ void mbar_arrive(uint32_t bar) {
    asm volatile("mbarrier.arrive.shared::cta.b64 _, [%0];" ::"r"(bar) : "memory");
}
__device__ __forceinline__ void mbar_arrive_cluster_pred(uint32_t addr, uint32_t pred) {
    asm volatile(
        "{\n.reg .pred p;\n"
        "setp.ne.u32 p, %1, 0;\n"
        "@p mbarrier.arrive.shared::cluster.b64 _, [%0];\n}\n" ::"r"(addr), "r"(pred) : "memory");
}
__device__ __forceinline__ void mbar_arrive_pred(uint32_t addr, uint32_t pred) {
    asm volatile(
        "{\n.reg .pred p;\n"
        "setp.ne.u32 p, %1, 0;\n"
        "@p mbarrier.arrive.shared::cta.b64 _, [%0];\n}\n" ::"r"(addr), "r"(pred) : "memory");
}
__device__ __forceinline__ uint32_t mapa(uint32_t addr, uint32_t cta) {
    uint32_t r;
    asm("mapa.shared::cluster.u32 %0, %1, %2;" : "=r"(r) : "r"(addr), "r"(cta));
    return r;
}
__device__ __forceinline__ void mbar_wait(uint32_t bar, uint32_t parity) {
    asm volatile(
        "{\n.reg .pred p;\n"
        "WAIT_LOOP:\n"
        "mbarrier.try_wait.parity.shared::cta.b64 p, [%0], %1;\n"
        "@p bra WAIT_DONE;\n"
        "bra WAIT_LOOP;\n"
        "WAIT_DONE:\n}\n" ::"r"(bar), "r"(parity) : "memory");
}
__device__ __forceinline__ bool elect_one() {
    uint32_t pred;
    asm volatile("{\n.reg .pred p;\nelect.sync _|p, 0xffffffff;\nselp.u32 %0, 1, 0, p;\n}\n" : "=r"(pred));
    return pred != 0;
}
__device__ __forceinline__ void tma_load_kv(uint32_t dst, const CUtensorMap* tm, int g, uint32_t bar) {
    asm volatile(
        "cp.async.bulk.tensor.4d.shared::cluster.global.mbarrier::complete_tx::bytes [%0], [%1, {%3, %3, %3, %4}], [%2];" ::"r"(dst),
        "l"(tm), "r"(bar), "r"(0), "r"(g)
        : "memory");
}
__device__ __forceinline__ void tma_load_kv_mc(uint32_t dst, const CUtensorMap* tm, int g, uint32_t bar) {
    asm volatile(
        "cp.async.bulk.tensor.4d.shared::cluster.global.mbarrier::complete_tx::bytes.multicast::cluster [%0], [%1, {%3, %3, %3, %4}], [%2], %5;" ::"r"(dst),
        "l"(tm), "r"(bar), "r"(0), "r"(g), "h"((uint16_t)3)
        : "memory");
}
__device__ __forceinline__ void tma_load_q(uint32_t dst, const CUtensorMap* tm, int g, int head, uint32_t bar) {
    asm volatile(
        "cp.async.bulk.tensor.5d.shared::cluster.global.mbarrier::complete_tx::bytes [%0], [%1, {%3, %3, %3, %4, %5}], [%2];" ::"r"(dst),
        "l"(tm), "r"(bar), "r"(0), "r"(g), "r"(head)
        : "memory");
}
__device__ __forceinline__ void tma_store_o(const CUtensorMap* tm, uint32_t src, int g, int head) {
    asm volatile("cp.async.bulk.tensor.5d.global.shared::cta.bulk_group [%0, {%2, %2, %2, %3, %4}], [%1];" ::"l"(tm),
                 "r"(src), "r"(0), "r"(g), "r"(head)
                 : "memory");
}
__device__ __forceinline__ void bulk_commit() { asm volatile("cp.async.bulk.commit_group;" ::: "memory"); }
__device__ __forceinline__ void bulk_wait_read() { asm volatile("cp.async.bulk.wait_group.read 0;" ::: "memory"); }
__device__ __forceinline__ void fence_async_smem() { asm volatile("fence.proxy.async.shared::cta;" ::: "memory"); }
__device__ __forceinline__ void stsm_x4(uint32_t addr, uint32_t r0, uint32_t r1, uint32_t r2, uint32_t r3) {
    asm volatile("stmatrix.sync.aligned.m8n8.x4.shared.b16 [%0], {%1, %2, %3, %4};" ::"r"(addr), "r"(r0), "r"(r1), "r"(r2), "r"(r3) : "memory");
}
__device__ __forceinline__ void ldsm_x4(uint32_t addr, uint32_t& r0, uint32_t& r1, uint32_t& r2, uint32_t& r3) {
    asm volatile("ldmatrix.sync.aligned.m8n8.x4.shared.b16 {%0, %1, %2, %3}, [%4];" : "=r"(r0), "=r"(r1), "=r"(r2), "=r"(r3) : "r"(addr) : "memory");
}
__device__ __forceinline__ void wgmma_fence() { asm volatile("wgmma.fence.sync.aligned;" ::: "memory"); }
__device__ __forceinline__ void wgmma_commit() { asm volatile("wgmma.commit_group.sync.aligned;" ::: "memory"); }
template <int N>
__device__ __forceinline__ void wgmma_wait() { asm volatile("wgmma.wait_group.sync.aligned %0;" ::"n"(N) : "memory"); }
__device__ __forceinline__ void bar_sync(int id, int n) { asm volatile("bar.sync %0, %1;" ::"r"(id), "r"(n) : "memory"); }
__device__ __forceinline__ void bar_arrive(int id, int n) { asm volatile("bar.arrive %0, %1;" ::"r"(id), "r"(n) : "memory"); }
__device__ __forceinline__ float ex2(float x) {
    float y;
    asm("ex2.approx.ftz.f32 %0, %1;" : "=f"(y) : "f"(x));
    return y;
}
__device__ __forceinline__ uint32_t pack_bf16(float lo, float hi) {
    uint32_t r;
    asm("cvt.rn.bf16x2.f32 %0, %1, %2;" : "=r"(r) : "f"(hi), "f"(lo));
    return r;
}
template <int N>
__device__ __forceinline__ void fence_regs(float (&r)[N]) {
#pragma unroll
    for (int i = 0; i < N; i++) asm volatile("" : "+f"(r[i])::"memory");
}
template <int N>
__device__ __forceinline__ void fence_regs(uint32_t (&r)[N]) {
#pragma unroll
    for (int i = 0; i < N; i++) asm volatile("" : "+r"(r[i])::"memory");
}
__device__ __forceinline__ void fence_regs2(float& a, float& b) { asm volatile("" : "+f"(a), "+f"(b)::"memory"); }
__device__ __forceinline__ uint64_t make_desc(uint32_t lo, uint32_t hi) { return ((uint64_t)hi << 32) | lo; }
constexpr uint32_t DESC_HI = (GRP_BYTES >> 4) | (1u << 30);

__device__ __forceinline__ void wgmma_qk(float (&d)[32], uint32_t a0, uint32_t a1, uint32_t a2, uint32_t a3, uint64_t descB) {
    asm volatile(
        "{\n.reg .pred p;\n"
        "setp.eq.b32 p, 0, 0;\n"
        "wgmma.mma_async.sync.aligned.m64n64k16.f32.bf16.bf16 "
        "{%0, %1, %2, %3, %4, %5, %6, %7, %8, %9, %10, %11, %12, %13, %14, %15, "
        "%16, %17, %18, %19, %20, %21, %22, %23, %24, %25, %26, %27, %28, %29, %30, %31}, "
        "{%32, %33, %34, %35}, %36, p, 1, 1, 0;\n}\n"
        : "+f"(d[0]), "+f"(d[1]), "+f"(d[2]), "+f"(d[3]), "+f"(d[4]), "+f"(d[5]), "+f"(d[6]), "+f"(d[7]),
          "+f"(d[8]), "+f"(d[9]), "+f"(d[10]), "+f"(d[11]), "+f"(d[12]), "+f"(d[13]), "+f"(d[14]), "+f"(d[15]),
          "+f"(d[16]), "+f"(d[17]), "+f"(d[18]), "+f"(d[19]), "+f"(d[20]), "+f"(d[21]), "+f"(d[22]), "+f"(d[23]),
          "+f"(d[24]), "+f"(d[25]), "+f"(d[26]), "+f"(d[27]), "+f"(d[28]), "+f"(d[29]), "+f"(d[30]), "+f"(d[31])
        : "r"(a0), "r"(a1), "r"(a2), "r"(a3), "l"(descB));
}

__device__ __forceinline__ void wgmma_qk_init(float (&d)[32], uint32_t a0, uint32_t a1, uint32_t a2, uint32_t a3, uint64_t descB) {
    asm volatile(
        "{\n.reg .pred p;\n"
        "setp.ne.b32 p, 0, 0;\n"
        "wgmma.mma_async.sync.aligned.m64n64k16.f32.bf16.bf16 "
        "{%0, %1, %2, %3, %4, %5, %6, %7, %8, %9, %10, %11, %12, %13, %14, %15, "
        "%16, %17, %18, %19, %20, %21, %22, %23, %24, %25, %26, %27, %28, %29, %30, %31}, "
        "{%32, %33, %34, %35}, %36, p, 1, 1, 0;\n}\n"
        : "=f"(d[0]), "=f"(d[1]), "=f"(d[2]), "=f"(d[3]), "=f"(d[4]), "=f"(d[5]), "=f"(d[6]), "=f"(d[7]),
          "=f"(d[8]), "=f"(d[9]), "=f"(d[10]), "=f"(d[11]), "=f"(d[12]), "=f"(d[13]), "=f"(d[14]), "=f"(d[15]),
          "=f"(d[16]), "=f"(d[17]), "=f"(d[18]), "=f"(d[19]), "=f"(d[20]), "=f"(d[21]), "=f"(d[22]), "=f"(d[23]),
          "=f"(d[24]), "=f"(d[25]), "=f"(d[26]), "=f"(d[27]), "=f"(d[28]), "=f"(d[29]), "=f"(d[30]), "=f"(d[31])
        : "r"(a0), "r"(a1), "r"(a2), "r"(a3), "l"(descB));
}

__device__ __forceinline__ void wgmma_pv(float (&d)[96], uint32_t a0, uint32_t a1, uint32_t a2, uint32_t a3, uint64_t descB) {
    asm volatile(
        "{\n.reg .pred p;\n"
        "setp.eq.b32 p, 0, 0;\n"
        "wgmma.mma_async.sync.aligned.m64n192k16.f32.bf16.bf16 "
        "{%0, %1, %2, %3, %4, %5, %6, %7, %8, %9, %10, %11, %12, %13, %14, %15, "
        "%16, %17, %18, %19, %20, %21, %22, %23, %24, %25, %26, %27, %28, %29, %30, %31, "
        "%32, %33, %34, %35, %36, %37, %38, %39, %40, %41, %42, %43, %44, %45, %46, %47, "
        "%48, %49, %50, %51, %52, %53, %54, %55, %56, %57, %58, %59, %60, %61, %62, %63, "
        "%64, %65, %66, %67, %68, %69, %70, %71, %72, %73, %74, %75, %76, %77, %78, %79, "
        "%80, %81, %82, %83, %84, %85, %86, %87, %88, %89, %90, %91, %92, %93, %94, %95}, "
        "{%96, %97, %98, %99}, %100, p, 1, 1, 1;\n}\n"
        : "+f"(d[0]), "+f"(d[1]), "+f"(d[2]), "+f"(d[3]), "+f"(d[4]), "+f"(d[5]), "+f"(d[6]), "+f"(d[7]),
          "+f"(d[8]), "+f"(d[9]), "+f"(d[10]), "+f"(d[11]), "+f"(d[12]), "+f"(d[13]), "+f"(d[14]), "+f"(d[15]),
          "+f"(d[16]), "+f"(d[17]), "+f"(d[18]), "+f"(d[19]), "+f"(d[20]), "+f"(d[21]), "+f"(d[22]), "+f"(d[23]),
          "+f"(d[24]), "+f"(d[25]), "+f"(d[26]), "+f"(d[27]), "+f"(d[28]), "+f"(d[29]), "+f"(d[30]), "+f"(d[31]),
          "+f"(d[32]), "+f"(d[33]), "+f"(d[34]), "+f"(d[35]), "+f"(d[36]), "+f"(d[37]), "+f"(d[38]), "+f"(d[39]),
          "+f"(d[40]), "+f"(d[41]), "+f"(d[42]), "+f"(d[43]), "+f"(d[44]), "+f"(d[45]), "+f"(d[46]), "+f"(d[47]),
          "+f"(d[48]), "+f"(d[49]), "+f"(d[50]), "+f"(d[51]), "+f"(d[52]), "+f"(d[53]), "+f"(d[54]), "+f"(d[55]),
          "+f"(d[56]), "+f"(d[57]), "+f"(d[58]), "+f"(d[59]), "+f"(d[60]), "+f"(d[61]), "+f"(d[62]), "+f"(d[63]),
          "+f"(d[64]), "+f"(d[65]), "+f"(d[66]), "+f"(d[67]), "+f"(d[68]), "+f"(d[69]), "+f"(d[70]), "+f"(d[71]),
          "+f"(d[72]), "+f"(d[73]), "+f"(d[74]), "+f"(d[75]), "+f"(d[76]), "+f"(d[77]), "+f"(d[78]), "+f"(d[79]),
          "+f"(d[80]), "+f"(d[81]), "+f"(d[82]), "+f"(d[83]), "+f"(d[84]), "+f"(d[85]), "+f"(d[86]), "+f"(d[87]),
          "+f"(d[88]), "+f"(d[89]), "+f"(d[90]), "+f"(d[91]), "+f"(d[92]), "+f"(d[93]), "+f"(d[94]), "+f"(d[95])
        : "r"(a0), "r"(a1), "r"(a2), "r"(a3), "l"(descB));
}

__device__ __forceinline__ void wgmma_pv_init(float (&d)[96], uint32_t a0, uint32_t a1, uint32_t a2, uint32_t a3, uint64_t descB) {
    asm volatile(
        "{\n.reg .pred p;\n"
        "setp.ne.b32 p, 0, 0;\n"
        "wgmma.mma_async.sync.aligned.m64n192k16.f32.bf16.bf16 "
        "{%0, %1, %2, %3, %4, %5, %6, %7, %8, %9, %10, %11, %12, %13, %14, %15, "
        "%16, %17, %18, %19, %20, %21, %22, %23, %24, %25, %26, %27, %28, %29, %30, %31, "
        "%32, %33, %34, %35, %36, %37, %38, %39, %40, %41, %42, %43, %44, %45, %46, %47, "
        "%48, %49, %50, %51, %52, %53, %54, %55, %56, %57, %58, %59, %60, %61, %62, %63, "
        "%64, %65, %66, %67, %68, %69, %70, %71, %72, %73, %74, %75, %76, %77, %78, %79, "
        "%80, %81, %82, %83, %84, %85, %86, %87, %88, %89, %90, %91, %92, %93, %94, %95}, "
        "{%96, %97, %98, %99}, %100, p, 1, 1, 1;\n}\n"
        : "=f"(d[0]), "=f"(d[1]), "=f"(d[2]), "=f"(d[3]), "=f"(d[4]), "=f"(d[5]), "=f"(d[6]), "=f"(d[7]),
          "=f"(d[8]), "=f"(d[9]), "=f"(d[10]), "=f"(d[11]), "=f"(d[12]), "=f"(d[13]), "=f"(d[14]), "=f"(d[15]),
          "=f"(d[16]), "=f"(d[17]), "=f"(d[18]), "=f"(d[19]), "=f"(d[20]), "=f"(d[21]), "=f"(d[22]), "=f"(d[23]),
          "=f"(d[24]), "=f"(d[25]), "=f"(d[26]), "=f"(d[27]), "=f"(d[28]), "=f"(d[29]), "=f"(d[30]), "=f"(d[31]),
          "=f"(d[32]), "=f"(d[33]), "=f"(d[34]), "=f"(d[35]), "=f"(d[36]), "=f"(d[37]), "=f"(d[38]), "=f"(d[39]),
          "=f"(d[40]), "=f"(d[41]), "=f"(d[42]), "=f"(d[43]), "=f"(d[44]), "=f"(d[45]), "=f"(d[46]), "=f"(d[47]),
          "=f"(d[48]), "=f"(d[49]), "=f"(d[50]), "=f"(d[51]), "=f"(d[52]), "=f"(d[53]), "=f"(d[54]), "=f"(d[55]),
          "=f"(d[56]), "=f"(d[57]), "=f"(d[58]), "=f"(d[59]), "=f"(d[60]), "=f"(d[61]), "=f"(d[62]), "=f"(d[63]),
          "=f"(d[64]), "=f"(d[65]), "=f"(d[66]), "=f"(d[67]), "=f"(d[68]), "=f"(d[69]), "=f"(d[70]), "=f"(d[71]),
          "=f"(d[72]), "=f"(d[73]), "=f"(d[74]), "=f"(d[75]), "=f"(d[76]), "=f"(d[77]), "=f"(d[78]), "=f"(d[79]),
          "=f"(d[80]), "=f"(d[81]), "=f"(d[82]), "=f"(d[83]), "=f"(d[84]), "=f"(d[85]), "=f"(d[86]), "=f"(d[87]),
          "=f"(d[88]), "=f"(d[89]), "=f"(d[90]), "=f"(d[91]), "=f"(d[92]), "=f"(d[93]), "=f"(d[94]), "=f"(d[95])
        : "r"(a0), "r"(a1), "r"(a2), "r"(a3), "l"(descB));
}

__device__ __forceinline__ void wgmma_rk(float (&d)[8], uint64_t descA, uint64_t descB) {
    asm volatile(
        "{\n.reg .pred p;\n"
        "setp.eq.b32 p, 0, 0;\n"
        "wgmma.mma_async.sync.aligned.m64n16k16.f32.bf16.bf16 "
        "{%0, %1, %2, %3, %4, %5, %6, %7}, "
        "%8, %9, p, 1, 1, 0, 0;\n}\n"
        : "+f"(d[0]), "+f"(d[1]), "+f"(d[2]), "+f"(d[3]), "+f"(d[4]), "+f"(d[5]), "+f"(d[6]), "+f"(d[7])
        : "l"(descA), "l"(descB));
}

__device__ __forceinline__ void wgmma_rk_init(float (&d)[8], uint64_t descA, uint64_t descB) {
    asm volatile(
        "{\n.reg .pred p;\n"
        "setp.ne.b32 p, 0, 0;\n"
        "wgmma.mma_async.sync.aligned.m64n16k16.f32.bf16.bf16 "
        "{%0, %1, %2, %3, %4, %5, %6, %7}, "
        "%8, %9, p, 1, 1, 0, 0;\n}\n"
        : "=f"(d[0]), "=f"(d[1]), "=f"(d[2]), "=f"(d[3]), "=f"(d[4]), "=f"(d[5]), "=f"(d[6]), "=f"(d[7])
        : "l"(descA), "l"(descB));
}

__device__ __forceinline__ void wgmma_rv(float (&d)[8], uint64_t descA, uint64_t descB) {
    asm volatile(
        "{\n.reg .pred p;\n"
        "setp.eq.b32 p, 0, 0;\n"
        "wgmma.mma_async.sync.aligned.m64n16k16.f32.bf16.bf16 "
        "{%0, %1, %2, %3, %4, %5, %6, %7}, "
        "%8, %9, p, 1, 1, 1, 0;\n}\n"
        : "+f"(d[0]), "+f"(d[1]), "+f"(d[2]), "+f"(d[3]), "+f"(d[4]), "+f"(d[5]), "+f"(d[6]), "+f"(d[7])
        : "l"(descA), "l"(descB));
}

struct Item { int head; int qt; int mc; };
__device__ __forceinline__ Item decode_item(uint32_t e, int rank) {
    Item it;
    it.mc = (e & 3) != 3;
    it.head = (e >> 2) + (it.mc ? 0 : rank);
    it.qt = 2 * (e & 3) + (it.mc ? rank : 0);
    return it;
}
__device__ __forceinline__ uint32_t first_entry(uint32_t c) { return (c / 3) * 4 + c % 3; }

__device__ __forceinline__ uint32_t k_addr(int e) { return SM_K + ((e + KROT) & 3) * BLK_BYTES; }
__device__ __forceinline__ void next_v(uint32_t& v) { v = v == SM_V + 2 * BLK_BYTES ? SM_V : v + BLK_BYTES; }
__device__ __forceinline__ void wait_blocks(uint32_t sbase, int e) { mbar_wait(sbase + BAR_FULL + 8 * (e & 3), e >> 2 & 1); }
__device__ __forceinline__ uint64_t k_desc(uint32_t sbase, int e) {
    return make_desc((((sbase & 0x3FFFF) + k_addr(e)) >> 4) | (1u << 16), DESC_HI);
}
__device__ __forceinline__ uint64_t v_desc(uint32_t sbase, uint32_t v) {
    return make_desc((((sbase & 0x3FFFF) + v) >> 4) | ((SLAB_BYTES >> 4) << 16), DESC_HI);
}
__device__ __forceinline__ constexpr uint32_t k_step(int k) { return (k & 3) == 3 ? (SLAB_BYTES >> 4) - 6 : 2; }

template <bool SPLIT>
__device__ __forceinline__ void issue_qk(float (&s)[32], uint32_t (&q)[48], uint32_t sbase, int e) {
    fence_regs(q);
    wgmma_fence();
    uint64_t desc = k_desc(sbase, e);
#pragma unroll
    for (int k = 0; k < 12; k++) {
        if (k == 0) wgmma_qk_init(s, q[0], q[1], q[2], q[3], desc);
        else wgmma_qk(s, q[4 * k], q[4 * k + 1], q[4 * k + 2], q[4 * k + 3], desc);
        if (k < 11) desc += k_step(k);
        if (SPLIT && (k & 3) == 3) wgmma_commit();
    }
    if (!SPLIT) wgmma_commit();
}
template <bool FIRST, bool WAIT = true, bool FENCE = false>
__device__ __forceinline__ void issue_pv(float (&o)[96], uint32_t (&p)[16], uint32_t sbase, int b, uint32_t& v) {
    if (WAIT) wait_blocks(sbase, b + 2);
    if (!FIRST) fence_regs(o);
    fence_regs(p);
    wgmma_fence();
    uint64_t desc = v_desc(sbase, v);
#pragma unroll
    for (int k = 0; k < 4; k++) {
        if (FIRST && k == 0) wgmma_pv_init(o, p[0], p[1], p[2], p[3], desc);
        else wgmma_pv(o, p[4 * k], p[4 * k + 1], p[4 * k + 2], p[4 * k + 3], desc);
        if (k < 3) desc += 2 * GRP_BYTES >> 4;
    }
    wgmma_commit();
    next_v(v);
}

__device__ __forceinline__ float opaque_copy(float x, uint32_t zero) { return x + __uint_as_float(zero); }

template <bool FIRST, int LO, int HI>
__device__ __forceinline__ void exp_range(float (&s)[32], float (&l)[2]) {
#pragma unroll
    for (int i = LO; i < HI; i++) s[i] = ex2(PRESCALE ? s[i] : s[i] * SCALE_LOG2E);
#pragma unroll
    for (int i = LO / 4; i < HI / 4; i++) {
        const float x = s[4 * i] + s[4 * i + 1], y = s[4 * i + 2] + s[4 * i + 3];
        if (FIRST && i == LO / 4) { l[0] = x; l[1] = y; }
        else { l[0] += x; l[1] += y; }
    }
}
__device__ __forceinline__ void pack_p(const float (&s)[32], uint32_t (&p)[16]) {
#pragma unroll
    for (int i = 0; i < 8; i++) {
        p[2 * i] = pack_bf16(s[4 * i], s[4 * i + 1]);
        p[2 * i + 1] = pack_bf16(s[4 * i + 2], s[4 * i + 3]);
    }
}
__device__ __forceinline__ bool sum_unsafe(float l) { return __float_as_uint(l) - SUM_LOW > SUM_HIGH - SUM_LOW; }

__device__ __forceinline__ void bb_boundary(uint32_t zero, float& x, float& y) {
    if (zero) {
#pragma unroll
        for (int i = 0; i < 12; i++) {
            asm volatile("mul.f32 %0, %0, %1;" : "+f"(x) : "f"(y));
            asm volatile("mul.f32 %0, %0, %1;" : "+f"(y) : "f"(x));
        }
    }
}
template <int CB>
__device__ __forceinline__ void load_q_slab(uint32_t (&q)[48], const uint32_t (&q_lane)[4]) {
#pragma unroll
    for (int k = 4 * CB; k < 4 * CB + 4; k++)
        ldsm_x4(q_lane[k & 3] + CB * SLAB_BYTES, q[4 * k], q[4 * k + 1], q[4 * k + 2], q[4 * k + 3]);
}
template <int LO, int HI>
__device__ __forceinline__ void scale_q(uint32_t (&q)[48]) {
    if (PRESCALE) {
#pragma unroll
        for (int i = LO; i < HI; i++)
            asm("{\n.reg .b32 t;\nmul.rn.bf16x2 t, %0, %1;\nfma.rn.bf16x2 %0, %0, %2, t;\n}\n" : "+r"(q[i]) : "r"(SCALE_LO), "r"(SCALE_HI));
    }
}
__device__ __forceinline__ void row_normalisers(float l0, float l1, float (&inv)[2][2], uint32_t& redo, uint32_t bit, uint32_t zero) {
    l0 += __shfl_xor_sync(0xffffffffu, l0, 1);
    l1 += __shfl_xor_sync(0xffffffffu, l1, 1);
    l0 += __shfl_xor_sync(0xffffffffu, l0, 2);
    l1 += __shfl_xor_sync(0xffffffffu, l1, 2);
    asm("rcp.approx.ftz.f32 %0, %1;" : "=f"(inv[0][0]) : "f"(l0));
    asm("rcp.approx.ftz.f32 %0, %1;" : "=f"(inv[1][0]) : "f"(l1));
    inv[0][1] = DUPI ? opaque_copy(inv[0][0], zero) : inv[0][0];
    inv[1][1] = DUPI ? opaque_copy(inv[1][0], zero) : inv[1][0];
    if (sum_unsafe(l0) | sum_unsafe(l1)) redo |= bit;
}
__device__ __forceinline__ void cvt_out(const float (&o)[96], int i, const float (&inv)[2][2], uint32_t& x, uint32_t& y) {
    x = pack_bf16(o[4 * i] * inv[0][0], o[4 * i + 1] * inv[0][1]);
    y = pack_bf16(o[4 * i + 2] * inv[1][0], o[4 * i + 3] * inv[1][1]);
}
__device__ __forceinline__ uint32_t stage_addr(const uint32_t (&stg_lane)[2], int g) { return stg_lane[g & 1] + (g >> 1) * SLAB_BYTES; }
template <int G0, int G1>
__device__ __forceinline__ void stage_output(const float (&o)[96], const float (&inv)[2][2], const uint32_t (&stg_lane)[2]) {
#pragma unroll
    for (int g = G0; g < G1; g++) {
        uint32_t x[4], y[4];
#pragma unroll
        for (int b = 0; b < 4; b++) cvt_out(o, 4 * g + b, inv, x[b], y[b]);
        if (GAPW & 1) wgmma_wait<0>();
        stsm_x4(stage_addr(stg_lane, g), x[0], x[1], x[2], x[3]);
        if (GAPW & 2) wgmma_wait<0>();
        stsm_x4(stage_addr(stg_lane, g) + GRP_BYTES, y[0], y[1], y[2], y[3]);
    }
}
template <int G0>
__device__ __forceinline__ void issue_qk_stage(float (&s)[32], uint32_t (&q)[48], uint32_t sbase, int e, const float (&o)[96], const float (&inv)[2][2],
                                               const uint32_t (&stg_lane)[2]) {
    constexpr int NS = 2 * (6 - G0);
    uint32_t x[7 - G0][4], y[7 - G0][4];
    fence_regs(q);
    wgmma_fence();
    uint64_t desc = k_desc(sbase, e);
#pragma unroll
    for (int k = 0; k < 12; k++) {
        if (k == 0) wgmma_qk_init(s, q[0], q[1], q[2], q[3], desc);
        else wgmma_qk(s, q[4 * k], q[4 * k + 1], q[4 * k + 2], q[4 * k + 3], desc);
        if (k < 11) desc += k_step(k);
        if (k == STG_CVTK) {
#pragma unroll
            for (int g = G0; g < 6; g++)
#pragma unroll
                for (int b = 0; b < 4; b++) cvt_out(o, 4 * g + b, inv, x[g - G0][b], y[g - G0][b]);
        }
        const int j = k - (12 - NS);
        if (j >= 0) {
            const int g = G0 + (j >> 1);
            if (j & 1) stsm_x4(stage_addr(stg_lane, g) + GRP_BYTES, y[g - G0][0], y[g - G0][1], y[g - G0][2], y[g - G0][3]);
            else stsm_x4(stage_addr(stg_lane, g), x[g - G0][0], x[g - G0][1], x[g - G0][2], x[g - G0][3]);
        }
    }
    wgmma_commit();
}
__device__ __forceinline__ void publish_output(uint32_t oready, int lane) {
    fence_async_smem();
    __syncwarp();
    mbar_arrive_pred(oready, lane == 0);
}

__device__ __forceinline__ void stsm_x4_t(uint32_t addr, uint32_t r0, uint32_t r1, uint32_t r2, uint32_t r3) {
    asm volatile("stmatrix.sync.aligned.m8n8.x4.trans.shared.b16 [%0], {%1, %2, %3, %4};" ::"r"(addr), "r"(r0), "r"(r1), "r"(r2), "r"(r3) : "memory");
}
__device__ __forceinline__ void issue_rem_qk(float (&s)[8], uint32_t sbase, int e) {
    wgmma_fence();
    uint64_t da = k_desc(sbase, e), db = make_desc((((sbase & 0x3FFFF) + SM_REM) >> 4) | (1u << 16), DESC_HI);
#pragma unroll
    for (int k = 0; k < 12; k++) {
        if (k == 0) wgmma_rk_init(s, da, db);
        else wgmma_rk(s, da, db);
        if (k < 11) { da += k_step(k); db += k_step(k); }
    }
    wgmma_commit();
}
__device__ __forceinline__ void issue_rem_pv(float (&o)[3][8], uint32_t pt, uint32_t sbase, int b, uint32_t& v) {
    wait_blocks(sbase, b + 2);
    fence_regs(o[0]); fence_regs(o[1]); fence_regs(o[2]);
    wgmma_fence();
    const uint64_t da = v_desc(sbase, v), db = make_desc((((sbase & 0x3FFFF) + pt) >> 4) | (1u << 16), (1024 >> 4) | (1u << 30));
#pragma unroll
    for (int k = 0; k < 4; k++)
#pragma unroll
        for (int m = 0; m < 3; m++) wgmma_rv(o[m], da + k * (2 * GRP_BYTES >> 4) + m * (SLAB_BYTES >> 4), db + 2 * k);
    wgmma_commit();
    next_v(v);
}
__device__ __forceinline__ void rem_softmax(float (&s)[8], float (&l)[4], uint32_t addr) {
#pragma unroll
    for (int i = 0; i < 8; i++) s[i] = ex2(s[i] * SCALE_LOG2E);
    stsm_x4_t(addr, pack_bf16(s[0], s[1]), pack_bf16(s[2], s[3]), pack_bf16(s[4], s[5]), pack_bf16(s[6], s[7]));
    fence_async_smem();
    l[0] += s[0] + s[2]; l[1] += s[1] + s[3]; l[2] += s[4] + s[6]; l[3] += s[5] + s[7];
}

__device__ __forceinline__ void mma_16816(float (&c)[4], uint32_t a0, uint32_t a1, uint32_t a2, uint32_t a3, uint32_t b0, uint32_t b1) {
    asm volatile("mma.sync.aligned.m16n8k16.row.col.f32.bf16.bf16.f32 {%0, %1, %2, %3}, {%4, %5, %6, %7}, {%8, %9}, {%0, %1, %2, %3};"
                 : "+f"(c[0]), "+f"(c[1]), "+f"(c[2]), "+f"(c[3]) : "r"(a0), "r"(a1), "r"(a2), "r"(a3), "r"(b0), "r"(b1));
}
__device__ __forceinline__ void exact_rows(const uint4* __restrict__ gq, const uint4* __restrict__ gk, const uint4* __restrict__ gv, uint4* __restrict__ go,
                                           int head, int row0, int lane) {
    constexpr int R = ROW_BYTES / 16;
    const int g = lane >> 2, c = lane & 3;
    const uint4* pq = gq + ((size_t)head * SQ + row0 + g) * R + c;
    uint4 qa[6], qb[6];
#pragma unroll
    for (int k = 0; k < 6; k++) { qa[k] = __ldg(pq + 4 * k); qb[k] = __ldg(pq + 8 * R + 4 * k); }
    float o[24][4], m[2] = {-INFINITY, -INFINITY}, l[2] = {0.f, 0.f};
#pragma unroll
    for (int i = 0; i < 24; i++) o[i][0] = o[i][1] = o[i][2] = o[i][3] = 0.f;
#pragma unroll 1
    for (int key0 = 0; key0 < SK; key0 += 16) {
        float s[2][4];
#pragma unroll
        for (int j = 0; j < 2; j++) {
            s[j][0] = s[j][1] = s[j][2] = s[j][3] = 0.f;
            const uint4* pk = gk + ((size_t)head * SK + key0 + 8 * j + g) * R + c;
#pragma unroll
            for (int k = 0; k < 6; k++) {
                const uint4 x = __ldg(pk + 4 * k);
                mma_16816(s[j], qa[k].x, qb[k].x, qa[k].y, qb[k].y, x.x, x.y);
                mma_16816(s[j], qa[k].z, qb[k].z, qa[k].w, qb[k].w, x.z, x.w);
            }
        }
#pragma unroll
        for (int h = 0; h < 2; h++) {
            float f = fmaxf(fmaxf(s[0][2 * h], s[0][2 * h + 1]), fmaxf(s[1][2 * h], s[1][2 * h + 1]));
            f = fmaxf(f, __shfl_xor_sync(0xffffffffu, f, 1));
            f = fmaxf(f, __shfl_xor_sync(0xffffffffu, f, 2));
            f = fmaxf(f, m[h]);
            const float ref = f == -INFINITY ? 0.f : f;
            const float sc = ex2((m[h] - ref) * SCALE_LOG2E);
            m[h] = f;
            l[h] *= sc;
#pragma unroll
            for (int j = 0; j < 2; j++)
#pragma unroll
                for (int e = 0; e < 2; e++) { s[j][2 * h + e] = ex2((s[j][2 * h + e] - ref) * SCALE_LOG2E); l[h] += s[j][2 * h + e]; }
#pragma unroll
            for (int i = 0; i < 24; i++) { o[i][2 * h] *= sc; o[i][2 * h + 1] *= sc; }
        }
        const uint32_t a0 = pack_bf16(s[0][0], s[0][1]), a1 = pack_bf16(s[0][2], s[0][3]), a2 = pack_bf16(s[1][0], s[1][1]), a3 = pack_bf16(s[1][2], s[1][3]);
        const uint4* pv = gv + ((size_t)head * SK + key0 + 2 * c) * R + g;
#pragma unroll
        for (int sl = 0; sl < 3; sl++) {
            const uint4 v0 = __ldg(pv + 8 * sl), v1 = __ldg(pv + R + 8 * sl), v2 = __ldg(pv + 8 * R + 8 * sl), v3 = __ldg(pv + 9 * R + 8 * sl);
            const uint32_t w0[4] = {v0.x, v0.y, v0.z, v0.w}, w1[4] = {v1.x, v1.y, v1.z, v1.w}, w2[4] = {v2.x, v2.y, v2.z, v2.w}, w3[4] = {v3.x, v3.y, v3.z, v3.w};
#pragma unroll
            for (int i = 0; i < 8; i++)
                mma_16816(o[8 * sl + i], a0, a1, a2, a3, __byte_perm(w0[i >> 1], w1[i >> 1], (i & 1) ? 0x7632 : 0x5410),
                          __byte_perm(w2[i >> 1], w3[i >> 1], (i & 1) ? 0x7632 : 0x5410));
        }
    }
#pragma unroll
    for (int h = 0; h < 2; h++) {
        l[h] += __shfl_xor_sync(0xffffffffu, l[h], 1);
        l[h] += __shfl_xor_sync(0xffffffffu, l[h], 2);
        const float inv = 1.0f / l[h];
        uint4* po = go + ((size_t)head * SQ + row0 + 8 * h + g) * R + 2 * c;
#pragma unroll
        for (int sl = 0; sl < 3; sl++)
#pragma unroll
            for (int e = 0; e < 2; e++) {
                uint32_t w[4];
#pragma unroll
                for (int i = 0; i < 4; i++) w[i] = pack_bf16(o[8 * sl + 2 * i][2 * h + e] * inv, o[8 * sl + 2 * i + 1][2 * h + e] * inv);
                po[8 * sl + e] = make_uint4(w[0], w[1], w[2], w[3]);
            }
    }
}

__global__ void __cluster_dims__(2, 1, 1) __launch_bounds__(384, 1)
attn_fwd_kernel(const __grid_constant__ CUtensorMap tmQ, const __grid_constant__ CUtensorMap tmK, const __grid_constant__ CUtensorMap tmV,
                const __grid_constant__ CUtensorMap tmO, const __grid_constant__ CUtensorMap tmR, const uint32_t zero,
                const uint4* __restrict__ gq, const uint4* __restrict__ gk, const uint4* __restrict__ gv, uint4* __restrict__ go) {
    extern __shared__ __align__(1024) uint8_t smem_raw[];
    const uint32_t sbase = smem_u32(smem_raw);
    const int warp_idx = __shfl_sync(0xffffffffu, threadIdx.x >> 5, 0);
    const int lane = threadIdx.x & 31;

    if (threadIdx.x == 0) {
        if (sbase & 1023) __trap();
        for (int i = 0; i < 4; i++) { mbar_init(sbase + BAR_FULL + 8 * i, 1); mbar_init(sbase + BAR_DONE + 8 * i, 4); }
        for (int i = 0; i < 2; i++) { mbar_init(sbase + BAR_QFULL + 8 * i, 1); mbar_init(sbase + BAR_OREADY + 8 * i, 4); mbar_init(sbase + BAR_STORED + 8 * i, 1); }
        mbar_init(sbase + BAR_DUMMY, 1);
        asm volatile("st.shared.v2.u32 [%0], {%1, %1};" ::"r"(sbase + SM_REDO), "r"(0) : "memory");
        asm volatile("fence.mbarrier_init.release.cluster;" ::: "memory");
    } else if (threadIdx.x == 32) {
        asm volatile("prefetch.tensormap [%0];" ::"l"(&tmQ) : "memory");
        asm volatile("prefetch.tensormap [%0];" ::"l"(&tmK) : "memory");
        asm volatile("prefetch.tensormap [%0];" ::"l"(&tmV) : "memory");
        asm volatile("prefetch.tensormap [%0];" ::"l"(&tmO) : "memory");
        asm volatile("prefetch.tensormap [%0];" ::"l"(&tmR) : "memory");
    }
    __syncthreads();
    asm volatile("barrier.cluster.arrive.relaxed.aligned;" ::: "memory");
    if (warp_idx < 3 && (int)(blockIdx.x >> 1) < EARLY_CLUSTERS) {
        if (elect_one()) {
            const int w = warp_idx - 1;
            const Item q = decode_item(first_entry(blockIdx.x >> 1), blockIdx.x & 1);
            if (warp_idx == 0) {
                mbar_expect_tx(sbase + BAR_FULL, BLK_BYTES);
                tma_load_kv(sbase + k_addr(0), &tmK, q.head * (SK / 8), sbase + BAR_FULL);
            } else {
                mbar_expect_tx(sbase + BAR_QFULL + 8 * w, BLK_BYTES);
                tma_load_q(sbase + SM_QO + w * BLK_BYTES, &tmQ, q.qt * 16 + w * 8, q.head, sbase + BAR_QFULL + 8 * w);
            }
        }
        __syncwarp();
    }
    asm volatile("barrier.cluster.wait.aligned;" ::: "memory");

#define ROLE_SETUP()                                                                          \
    uint32_t bid_;                                                                            \
    asm volatile("mov.u32 %0, %%ctaid.x;" : "=r"(bid_));                                      \
    const uint32_t rank = bid_ & 1;                                                           \
    const int cluster_id = bid_ >> 1;                                                         \
    const uint16_t* sched = SCHED[cluster_id];

    if (warp_idx < 4) {
        asm volatile("setmaxnreg.dec.sync.aligned.u32 %0;" ::"n"(PRODUCER_REGS));
        ROLE_SETUP()
        if (cluster_id >= EARLY_CLUSTERS) {
            const uint32_t t0 = clock(), d = (cluster_id - EARLY_CLUSTERS + 1) * START_STEP;
            while ((uint32_t)clock() - t0 < d) __nanosleep(20);
        }
        if (warp_idx == 0) {
            if (elect_one()) {
                auto load = [&](const CUtensorMap* tm, uint32_t owner, const Item& it, int blk, uint32_t dst, uint32_t full) {
                    const int grp = it.head * (SK / 8) + blk * 8;
                    if (!it.mc) tma_load_kv(sbase + dst, tm, grp, full);
                    else if (rank == owner) tma_load_kv_mc(sbase + dst, tm, grp, full);
                };
                Item iv = decode_item(first_entry(cluster_id), rank), ik = iv;
                for (int e = cluster_id < EARLY_CLUSTERS; e < 2; e++) {
                    mbar_expect_tx(sbase + BAR_FULL + 8 * e, BLK_BYTES);
                    load(&tmK, 0, ik, e, k_addr(e), sbase + BAR_FULL + 8 * e);
                }
                uint32_t v = SM_V;
                bool more = true;
                for (int t = 1; more; t++) {
#pragma unroll 1
                    for (int e = 2; e < NBLK + 2; e++) {
                        if (e == NBLK) { more = t < sched[SCHED_COUNT]; ik = decode_item(sched[t], rank); }
                        const uint32_t full = sbase + BAR_FULL + 8 * (e & 3);
                        mbar_wait(full + (BAR_DONE - BAR_FULL), ~e >> 2 & 1);
                        mbar_expect_tx(full, more ? 2 * BLK_BYTES : BLK_BYTES);
                        load(&tmV, 1, iv, e - 2, v, full);
                        if (more) load(&tmK, 0, ik, e & 7, k_addr(e), full);
                        next_v(v);
                    }
                    iv = ik;
                }
            }
        } else if (warp_idx < 3) {
            if (elect_one()) {
                const int w = warp_idx - 1;
                const uint32_t buf = sbase + SM_QO + w * BLK_BYTES;
                const uint32_t qfull = sbase + BAR_QFULL + 8 * w, oready = sbase + BAR_OREADY + 8 * w;
                if (cluster_id >= EARLY_CLUSTERS) {
                    const Item q = decode_item(first_entry(cluster_id), rank);
                    mbar_expect_tx(qfull, BLK_BYTES);
                    tma_load_q(buf, &tmQ, q.qt * 16 + w * 8, q.head, qfull);
                }
                const int n_items = sched[SCHED_COUNT];
                for (int r = 0; r <= n_items; r++) {
                    const Item o = decode_item(sched[r > 0 ? r - 1 : 0], rank), q = decode_item(sched[r + 1], rank);
                    mbar_wait(oready, r & 1);
                    if (r > 0) {
                        tma_store_o(&tmO, (MINI && w == 1 && !o.mc) ? sbase + SM_REM : buf, o.qt * 16 + w * 8, o.head);
                        bulk_commit();
                        bulk_wait_read();
                    }
                    if (r + 1 < n_items) {
                        const bool rem = MINI && w == 1 && !q.mc;
                        mbar_expect_tx(qfull, rem ? REM_BYTES : BLK_BYTES);
                        tma_load_q(rem ? sbase + SM_REM : buf, rem ? &tmR : &tmQ, q.qt * 16 + w * 8, q.head, qfull);
                    } else if (r + 1 == n_items) {
                        mbar_arrive(qfull);
                    }
                }
                uint32_t redo;
                asm volatile("ld.shared.u32 %0, [%1];" : "=r"(redo) : "r"(sbase + SM_REDO + 4 * w) : "memory");
                if (redo) {
                    asm volatile("cp.async.bulk.wait_group 0;\nfence.proxy.async;" ::: "memory");
                    mbar_arrive(sbase + BAR_STORED + 8 * w);
                }
            }
        }
        else if (T_KVPF && elect_one()) {
            const int n_items = sched[SCHED_COUNT];
            const char* kv = reinterpret_cast<const char*>(rank ? gv : gk);
#pragma unroll 1
            for (int e = 4; e < NBLK * n_items; e++) {
                mbar_wait(sbase + BAR_DONE + 8 * (e & 3), ~e >> 2 & 1);
                const int x = e + T_KVPF - 2 * rank;
                const uint32_t it = sched[x >> 3];
                if (x >> 3 < n_items && (it & 3) != 3)
                    asm volatile("cp.async.bulk.prefetch.L2.global [%0], %1;" ::"l"(kv + ((it >> 2) * 24 + (x & 7) * 3 + (it & 3)) * (BLK_BYTES / 3)), "r"(BLK_BYTES / 3) : "memory");
            }
        }
    } else {
        asm volatile("setmaxnreg.inc.sync.aligned.u32 %0;" ::"n"(CONSUMER_REGS));
        ROLE_SETUP()
        const int wg = (warp_idx >> 2) - 1;
        const int tw = threadIdx.x & 127;
        const int bar_me = 1 + wg, bar_other = 2 - wg;
        const uint32_t qo = sbase + SM_QO + wg * BLK_BYTES + (warp_idx & 3) * 2 * GRP_BYTES;
        uint32_t q_lane[4], stg_lane[2];
#pragma unroll
        for (int i = 0; i < 4; i++)
            q_lane[i] = __shfl_sync(0xffffffffu, (qo + (lane & 7) * 128 + ((lane >> 3) & 1) * GRP_BYTES + (((lane >> 4) ^ (lane & 7)) << 4)) ^ (i * 32), lane);
#pragma unroll
        for (int i = 0; i < 2; i++) stg_lane[i] = __shfl_sync(0xffffffffu, (qo + (lane & 7) * 128 + (((lane >> 3) ^ (lane & 7)) << 4)) ^ (i * 64), lane);
        const uint32_t qfull = sbase + BAR_QFULL + 8 * wg, oready = sbase + BAR_OREADY + 8 * wg;

        float o[96], s[32], l[2];
        uint32_t q[48], p[16];
        uint32_t redo = 0;
        uint32_t v = SM_V;
        const uint32_t rel_pred = (tw == 0 || tw == 32) ? 1u : 0u;
        const uint32_t rel_base = __shfl_sync(0xffffffffu, mapa(sbase, warp_idx & 1) + BAR_DONE, 0);
        auto release = [&](int e) { mbar_arrive_cluster_pred(rel_base + 8 * (e & 3), rel_pred); };

        if (wg == 1) bar_arrive(1, 256);

        mbar_wait(qfull, 0);
        load_q_slab<0>(q, q_lane); load_q_slab<1>(q, q_lane); load_q_slab<2>(q, q_lane);
        scale_q<0, 48>(q);
        wait_blocks(sbase, 0);
        bar_sync(bar_me, 256);
        issue_qk<false>(s, q, sbase, 0);
        bar_arrive(bar_other, 256);
        const int n_items = sched[SCHED_COUNT];
        const uint32_t breaks = __shfl_sync(0xffffffffu, ((MINI && wg == 1) ? *reinterpret_cast<const uint32_t*>(sched + SCHED_SHORT) : 0u) | 1u << n_items, 0);
        wgmma_wait<0>();
        fence_regs(s);
        release(0);
        exp_range<true, 0, 32>(s, l);
        pack_p(s, p);
        wait_blocks(sbase, 1);
        float inv[2][2] = {{0.f, 0.f}, {0.f, 0.f}};
#pragma unroll
        for (int i = 0; i < 96; i++) o[i] = 0.f;

#define PHASE_TAIL(B_, FIRST_, NP_, MID_, LATE_, VW_) {                                        \
        exp_range<FIRST_, 0, NP_>(s, l);                                                       \
        MID_;                                                                                  \
        fence_regs(s);                                                                         \
        if (VW_) wait_blocks(sbase, (B_) + 3);                                                 \
        else mbar_wait(sbase + BAR_DUMMY, 1);                                                  \
        wgmma_wait<0>();                                                                       \
        fence_regs(o);                                                                         \
        fence_regs(p);                                                                         \
        release((B_) + 1);                                                                     \
        if (NP_ < 32) { fence_regs(s); exp_range<false, NP_, 32>(s, l); }                      \
        pack_p(s, p);                                                                          \
        LATE_; }

        for (int t = 0;; t++) {
            const bool has_next = t + 1 < n_items, chain = !(breaks >> t & 2);
            wait_blocks(sbase, 2);
            bar_sync(bar_me, 256);
            issue_qk_stage<STAGE_SPLIT>(s, q, sbase, 1, o, inv, stg_lane);
            issue_pv<true, false>(o, p, sbase, 0, v);
            bar_arrive(bar_other, 256);
            wgmma_wait<1>();
            fence_regs(s);
            PHASE_TAIL(0, false, 32, , , VW_EARLY)
#pragma unroll 1
            for (int b = 1; b < NBLK - 2; b++) {
                bar_sync(bar_me, 256);
                issue_qk<false>(s, q, sbase, b + 1);
                if (b == PUB_B) publish_output(oready, lane);
                issue_pv<false, !VW_EARLY>(o, p, sbase, b, v);
                bar_arrive(bar_other, 256);
                wgmma_wait<1>();
                fence_regs(s);
                PHASE_TAIL(b, false, 32, , , VW_EARLY)
            }
            bar_sync(bar_me, 256);
            issue_qk<true>(s, q, sbase, 7);
            mbar_wait(qfull, ~t & 1);
            wgmma_wait<2>();
            load_q_slab<0>(q, q_lane);
            if (!VW_EARLY) bb_boundary(zero, l[0], l[1]);
            issue_pv<false, !VW_EARLY>(o, p, sbase, 6, v);
            bar_arrive(bar_other, 256);
            wgmma_wait<2>();
            load_q_slab<1>(q, q_lane);
            bb_boundary(zero, l[0], l[1]);
            wgmma_wait<1>();
            fence_regs(s);
            load_q_slab<2>(q, q_lane);
            bb_boundary(zero, l[0], l[1]);
            PHASE_TAIL(6, false, 32, (scale_q<0, QS_POS>(q)), (scale_q<QS_POS, 48>(q)), VW_EARLY)
            if (chain) {
                bar_sync(bar_me, 256);
                issue_qk<false>(s, q, sbase, 0);
                issue_pv<false, !VW_EARLY>(o, p, sbase, 7, v);
                bar_arrive(bar_other, 256);
                row_normalisers(l[0], l[1], inv, redo, 1u << t, zero);
                fence_regs2(inv[0][1], inv[1][1]);
                wgmma_wait<1>();
                fence_regs(s);
                PHASE_TAIL(7, true, NPRE7, , (stage_output<0, STAGE_SPLIT>(o, inv, stg_lane)), false)
                continue;
            }
            if (!MINI || !has_next) {
                bar_sync(bar_me, 256);
                issue_pv<false, !VW_EARLY, true>(o, p, sbase, 7, v);
                if (wg == 0) bar_arrive(bar_other, 256);
                row_normalisers(l[0], l[1], inv, redo, 1u << t, zero);
                wgmma_wait<0>();
                fence_regs(o);
                stage_output<0, 6>(o, inv, stg_lane);
                break;
            }
            float rs[8];
            bar_sync(bar_me, 256);
            issue_rem_qk(rs, sbase, 0);
            issue_pv<false, !VW_EARLY, true>(o, p, sbase, 7, v);
            bar_arrive(bar_other, 256);
            row_normalisers(l[0], l[1], inv, redo, 1u << t, zero);
            t++;
            wgmma_wait<1>();
            fence_regs(rs);
            const uint32_t t_lane = sbase + (lane & 7) * 128 + ((((warp_idx & 3) * 2 + (lane >> 3 & 1)) ^ (lane & 7)) << 4);
            const uint32_t pt_lane = t_lane + SM_PT + (lane >> 4) * 1024;
            float ro[3][8], rl[4] = {0.f, 0.f, 0.f, 0.f};
            rem_softmax(rs, rl, pt_lane);
#pragma unroll
            for (int i = 0; i < 8; i++) ro[0][i] = ro[1][i] = ro[2][i] = 0.f;
            mbar_wait(sbase + BAR_DUMMY, 1);
            wgmma_wait<0>();
            fence_regs(o);
            release(0);
            stage_output<0, 6>(o, inv, stg_lane);
            publish_output(oready, lane);
            fence_regs(ro[0]); fence_regs(ro[1]); fence_regs(ro[2]);
#pragma unroll 1
            for (int b = 0; b < NBLK - 1; b++) {
                bar_sync(bar_me, 256);
                issue_rem_qk(rs, sbase, b + 1);
                issue_rem_pv(ro, SM_PT + (b & 1) * 2048, sbase, b, v);
                bar_arrive(bar_other, 256);
                wgmma_wait<1>();
                fence_regs(rs);
                rem_softmax(rs, rl, pt_lane + (~b & 1) * 2048);
                mbar_wait(sbase + BAR_DUMMY, 1);
                wgmma_wait<0>();
                fence_regs(ro[0]); fence_regs(ro[1]); fence_regs(ro[2]);
                release(b + 1);
            }
            auto share_sums = [&]() {
#pragma unroll
                for (int i = 0; i < 4; i++) {
                    rl[i] += __shfl_xor_sync(0xffffffffu, rl[i], 4);
                    rl[i] += __shfl_xor_sync(0xffffffffu, rl[i], 8);
                    rl[i] += __shfl_xor_sync(0xffffffffu, rl[i], 16);
                }
                if (lane < 4) asm volatile("st.shared.v4.f32 [%0], {%1, %2, %3, %4};" ::"r"(sbase + SM_LSUM + (warp_idx & 3) * 64 + lane * 16), "f"(rl[0]), "f"(rl[1]), "f"(rl[2]), "f"(rl[3]) : "memory");
            };
            auto rem_normalisers = [&]() {
#pragma unroll
                for (int w = 0; w < 4; w++) {
                    float x[4];
                    asm volatile("ld.shared.v4.f32 {%0, %1, %2, %3}, [%4];" : "=f"(x[0]), "=f"(x[1]), "=f"(x[2]), "=f"(x[3]) : "r"(sbase + SM_LSUM + w * 64 + (lane & 3) * 16) : "memory");
#pragma unroll
                    for (int i = 0; i < 4; i++) rl[i] = w ? rl[i] + x[i] : x[i];
                }
                if (sum_unsafe(rl[0]) | sum_unsafe(rl[1]) | sum_unsafe(rl[2]) | sum_unsafe(rl[3])) redo |= 1u << t;
#pragma unroll
                for (int i = 0; i < 4; i++) asm("rcp.approx.ftz.f32 %0, %0;" : "+f"(rl[i]));
            };
            auto rem_stage = [&]() {
                wgmma_wait<0>();
                fence_regs(ro[0]); fence_regs(ro[1]); fence_regs(ro[2]);
                release(0);
#pragma unroll
                for (int m = 0; m < 3; m++)
                    stsm_x4_t(t_lane + SM_REM + (lane >> 4) * GRP_BYTES + m * SLAB_BYTES, pack_bf16(ro[m][0] * rl[0], ro[m][1] * rl[1]), pack_bf16(ro[m][2] * rl[0], ro[m][3] * rl[1]),
                              pack_bf16(ro[m][4] * rl[2], ro[m][5] * rl[3]), pack_bf16(ro[m][6] * rl[2], ro[m][7] * rl[3]));
            };
            if (t + 1 == n_items) {
                share_sums();
                bar_sync(bar_me, 256);
                issue_rem_pv(ro, SM_PT + 2048, sbase, 7, v);
                rem_normalisers();
                rem_stage();
                break;
            }
            mbar_wait(qfull, ~t & 1);
            load_q_slab<0>(q, q_lane); load_q_slab<1>(q, q_lane); load_q_slab<2>(q, q_lane);
            share_sums();
            scale_q<0, 48>(q);
            bar_sync(bar_me, 256);
            issue_qk<false>(s, q, sbase, 0);
            issue_rem_pv(ro, SM_PT + 2048, sbase, 7, v);
            bar_arrive(bar_other, 256);
            rem_normalisers();
            wgmma_wait<1>();
            fence_regs(s);
            exp_range<true, 0, 32>(s, l);
            pack_p(s, p);
            mbar_wait(sbase + BAR_DUMMY, 1);
            rem_stage();
        }
        redo = __reduce_or_sync(0xffffffffu, redo);
        if (redo) asm volatile("st.shared.u32 [%0], %1;" ::"r"(sbase + SM_REDO + 4 * wg), "r"(1) : "memory");
        publish_output(oready, lane);
        if (redo) {
            mbar_wait(sbase + BAR_STORED + 8 * wg, 0);
            asm volatile("fence.proxy.async;" ::: "memory");
            for (; redo; redo &= redo - 1) {
                const Item it = decode_item(sched[__ffs(redo) - 1], rank);
                const int row0 = it.qt * 128 + (warp_idx - 4) * 16;
                if (row0 < SQ) exact_rows(gq, gk, gv, go, it.head, row0, lane);
            }
        }
    }
    asm volatile("barrier.cluster.arrive.relaxed.aligned;\nbarrier.cluster.wait.aligned;" ::: "memory");
}

typedef CUresult (*EncodeTiledFn)(CUtensorMap*, CUtensorMapDataType, cuuint32_t, void*, const cuuint64_t*, const cuuint64_t*,
                                  const cuuint32_t*, const cuuint32_t*, CUtensorMapInterleave, CUtensorMapSwizzle,
                                  CUtensorMapL2promotion, CUtensorMapFloatOOBfill);

}

extern "C" void kernel_launch(void* const* d_in, const int* in_sizes, int n_in, void* d_out, int out_size) {
    (void)in_sizes; (void)n_in; (void)out_size;
    static CUtensorMap tmQ, tmK, tmV, tmO, tmR;
    static void* cached[4] = {nullptr, nullptr, nullptr, nullptr};
    if (cached[0] != d_in[0] || cached[1] != d_in[1] || cached[2] != d_in[2] || cached[3] != d_out) {
        void* fn = nullptr;
        cudaDriverEntryPointQueryResult qr;
        cudaGetDriverEntryPoint("cuTensorMapEncodeTiled", &fn, cudaEnableDefault, &qr);
        EncodeTiledFn enc = (EncodeTiledFn)fn;
        const cuuint32_t es[5] = {1, 1, 1, 1, 1};
        const cuuint32_t box[5] = {64, 8, 3, 8, 1};
        const cuuint32_t box_rem[5] = {64, 8, 3, 2, 1};
        {
            cuuint64_t gd[5] = {64, 8, 3, SQ / 8, NHEADS};
            cuuint64_t gs[4] = {ROW_BYTES, 128, 8 * ROW_BYTES, (cuuint64_t)SQ * ROW_BYTES};
            enc(&tmQ, CU_TENSOR_MAP_DATA_TYPE_BFLOAT16, 5, d_in[0], gd, gs, box, es, CU_TENSOR_MAP_INTERLEAVE_NONE,
                CU_TENSOR_MAP_SWIZZLE_128B, CU_TENSOR_MAP_L2_PROMOTION_NONE, CU_TENSOR_MAP_FLOAT_OOB_FILL_NONE);
            enc(&tmR, CU_TENSOR_MAP_DATA_TYPE_BFLOAT16, 5, d_in[0], gd, gs, box_rem, es, CU_TENSOR_MAP_INTERLEAVE_NONE,
                CU_TENSOR_MAP_SWIZZLE_128B, CU_TENSOR_MAP_L2_PROMOTION_NONE, CU_TENSOR_MAP_FLOAT_OOB_FILL_NONE);
            enc(&tmO, CU_TENSOR_MAP_DATA_TYPE_BFLOAT16, 5, d_out, gd, gs, box, es, CU_TENSOR_MAP_INTERLEAVE_NONE,
                CU_TENSOR_MAP_SWIZZLE_128B, CU_TENSOR_MAP_L2_PROMOTION_NONE, CU_TENSOR_MAP_FLOAT_OOB_FILL_NONE);
        }
        {
            cuuint64_t gd[4] = {64, 8, 3, (cuuint64_t)NHEADS * SK / 8};
            cuuint64_t gs[3] = {ROW_BYTES, 128, 8 * ROW_BYTES};
            enc(&tmK, CU_TENSOR_MAP_DATA_TYPE_BFLOAT16, 4, d_in[1], gd, gs, box, es, CU_TENSOR_MAP_INTERLEAVE_NONE,
                CU_TENSOR_MAP_SWIZZLE_128B, CU_TENSOR_MAP_L2_PROMOTION_NONE, CU_TENSOR_MAP_FLOAT_OOB_FILL_NONE);
            enc(&tmV, CU_TENSOR_MAP_DATA_TYPE_BFLOAT16, 4, d_in[2], gd, gs, box, es, CU_TENSOR_MAP_INTERLEAVE_NONE,
                CU_TENSOR_MAP_SWIZZLE_128B, CU_TENSOR_MAP_L2_PROMOTION_NONE, CU_TENSOR_MAP_FLOAT_OOB_FILL_NONE);
        }
        cudaFuncSetAttribute(attn_fwd_kernel, cudaFuncAttributeMaxDynamicSharedMemorySize, SMEM_BYTES);
        cached[0] = d_in[0]; cached[1] = d_in[1]; cached[2] = d_in[2]; cached[3] = d_out;
    }
    attn_fwd_kernel<<<2 * NUM_CLUSTERS, 384, SMEM_BYTES, cudaStreamPerThread>>>(tmQ, tmK, tmV, tmO, tmR, 0u, (const uint4*)d_in[0], (const uint4*)d_in[1],
                                                                                (const uint4*)d_in[2], (uint4*)d_out);
}
```

```cpp
#include <cuda_runtime.h>
#include <cuda_bf16.h>
#include <cuda.h>
#include <stdint.h>

namespace {

constexpr int NHEADS = 512;
constexpr int SQ = 848;
constexpr int SK = 512;
constexpr int DH = 192;
constexpr int ROW_BYTES = DH * 2;
constexpr int NBLK = SK / 64;
constexpr int NUM_CLUSTERS = 66;

constexpr uint32_t GRP_BYTES = 3072, SLAB_BYTES = 1024;
constexpr uint32_t BLK_BYTES = 64 * ROW_BYTES;
constexpr uint32_t REM_BYTES = 16 * ROW_BYTES;
constexpr uint32_t SM_BASE = 1024;
constexpr uint32_t SM_BAR = 0;
constexpr uint32_t SM_REM = 1024;
constexpr uint32_t SM_V = SM_REM + REM_BYTES;
constexpr uint32_t SM_K = SM_V + 3 * BLK_BYTES;
constexpr uint32_t SM_QO = SM_K + 4 * BLK_BYTES;
constexpr uint32_t SM_PT = SM_QO + 2 * BLK_BYTES;
constexpr uint32_t SMEM_BYTES = SM_PT + 2 * 2048;
#define T_KVPF 4
#define KROT 2
constexpr uint32_t BAR_FULL = SM_BAR;
constexpr uint32_t BAR_DONE = BAR_FULL + 32;
constexpr uint32_t BAR_QFULL = BAR_DONE + 32;
constexpr uint32_t BAR_OREADY = BAR_QFULL + 16;
constexpr uint32_t BAR_STORED = BAR_OREADY + 16;
constexpr uint32_t BAR_DUMMY = BAR_STORED + 16;
constexpr uint32_t BAR_REMFREE = BAR_DUMMY + 8;
constexpr uint32_t BAR_SUMS = BAR_REMFREE + 8;
constexpr uint32_t SM_REDO = BAR_SUMS + 8;
static_assert(SMEM_BYTES <= 232448, "smem");

constexpr int PRODUCER_REGS = 24, CONSUMER_REGS = 240;
#define STAGE_SPLIT 8
#define STG_CVTK 3
#define STG_K0 8
#define STG_DK 1
#define MS0 1
#define SK0 0
#define SDK 2
#define XN 32
#define NRM 1
#define PUB_B 1
#define GAPW 3
#define NPRE7 32
#define QS_POS 32
constexpr float SCALE_LOG2E = 0.07216878364870323f * 1.4426950408889634f;
constexpr uint32_t SCALE_HI = 0x3DD53DD5u, SCALE_LO = 0x38EE38EEu;
constexpr uint32_t SUM_LOW = (127u - 14u) << 23, SUM_HIGH = (127u + 32u) << 23;

constexpr int EARLY_CLUSTERS = 10, START_STEP = 70;
constexpr int SCHED_COUNT = 29, SCHED_BREAKS = 30;
__constant__ __align__(8) uint16_t SCHED[NUM_CLUSTERS][36] = {
    {0, 3, 152, 228, 295, 378, 456, 523, 605, 681, 756, 823, 904, 981, 1060, 1115, 1197, 1277, 1354, 1430, 1508, 1567, 1652, 1733, 1813, 1889, 1939, 2032, 0, 28, 2064, 4128, 32898, 37888, 0, 0},
    {1, 11, 153, 229, 303, 380, 443, 529, 606, 682, 757, 832, 908, 975, 1061, 1134, 1209, 1275, 1356, 1432, 1509, 1588, 1655, 1734, 1779, 1864, 1949, 2033, 0, 28, 8208, 4160, 66, 37122, 0, 0},
    {2, 19, 154, 230, 305, 381, 458, 537, 607, 686, 747, 833, 909, 985, 1039, 1136, 1210, 1286, 1347, 1433, 1503, 1574, 1653, 1736, 1787, 1865, 1950, 2034, 0, 28, 16640, 4112, 1026, 37124, 0, 0},
    {4, 27, 156, 232, 306, 382, 460, 538, 614, 693, 767, 840, 916, 992, 1059, 1141, 1218, 1293, 1367, 1441, 1515, 1589, 1666, 1735, 1814, 1883, 1952, 2036, 0, 28, 1024, 4228, 16386, 37392, 0, 0},
    {5, 35, 157, 233, 308, 384, 461, 535, 609, 667, 758, 834, 910, 986, 1064, 1127, 1212, 1288, 1365, 1435, 1510, 1575, 1654, 1737, 1795, 1866, 1953, 2037, 0, 28, 32896, 4128, 514, 37128, 0, 0},
    {6, 88, 168, 227, 309, 383, 457, 532, 595, 684, 760, 831, 905, 982, 1062, 1137, 1213, 1283, 1357, 1434, 1512, 1583, 1656, 1691, 1784, 1868, 1954, 2038, 0, 28, 2080, 4128, 264, 36994, 0, 0},
    {8, 43, 158, 223, 304, 371, 454, 530, 608, 685, 761, 836, 912, 988, 1047, 1138, 1203, 1278, 1358, 1436, 1513, 1590, 1668, 1743, 1816, 1890, 1947, 2040, 0, 28, 16392, 4224, 34, 37889, 0, 0},
    {9, 51, 160, 234, 310, 385, 462, 540, 615, 688, 755, 837, 913, 989, 1055, 1140, 1214, 1289, 1355, 1437, 1514, 1592, 1669, 1742, 1820, 1895, 1969, 2027, 0, 28, 16640, 4608, 1026, 38916, 0, 0},
    {10, 89, 169, 246, 325, 387, 464, 541, 616, 694, 770, 839, 917, 979, 1065, 1135, 1216, 1290, 1366, 1442, 1517, 1593, 1659, 1744, 1815, 1892, 1955, 2041, 0, 28, 34816, 4352, 8224, 37952, 0, 0},
    {12, 90, 147, 236, 312, 386, 455, 533, 610, 675, 762, 838, 914, 990, 1066, 1143, 1217, 1292, 1368, 1444, 1518, 1594, 1667, 1745, 1823, 1893, 1970, 2035, 0, 28, 32832, 4352, 516, 38976, 0, 0},
    {13, 92, 172, 250, 307, 389, 466, 544, 620, 698, 774, 853, 933, 1014, 1093, 1174, 1252, 1330, 1409, 1489, 1569, 1623, 1696, 1774, 1853, 1937, 2017, 0, 0, 27, 0, 34848, 16, 2048, 0, 0},
    {14, 59, 161, 237, 314, 390, 468, 545, 621, 700, 776, 854, 934, 1016, 1096, 1178, 1256, 1333, 1412, 1463, 1538, 1618, 1698, 1777, 1857, 1941, 2021, 0, 0, 27, 0, 34824, 2, 2048, 0, 0},
    {16, 93, 173, 252, 332, 412, 475, 546, 624, 702, 778, 857, 936, 1017, 1097, 1180, 1257, 1334, 1399, 1462, 1541, 1621, 1701, 1780, 1860, 1944, 2025, 0, 0, 27, 0, 34820, 64, 2048, 0, 0},
    {17, 67, 162, 238, 316, 392, 463, 534, 612, 689, 764, 841, 918, 994, 1070, 1146, 1224, 1304, 1382, 1464, 1542, 1622, 1702, 1781, 1861, 1946, 2029, 0, 0, 27, 64, 34816, 2, 2048, 0, 0},
    {18, 94, 174, 253, 333, 413, 492, 570, 649, 732, 809, 890, 969, 1048, 1121, 1200, 1259, 1338, 1416, 1496, 1577, 1658, 1738, 1817, 1894, 1967, 2044, 0, 0, 27, 0, 35328, 0, 2049, 0, 0},
    {20, 96, 155, 240, 317, 393, 469, 548, 625, 687, 765, 842, 921, 997, 1073, 1149, 1226, 1306, 1385, 1466, 1545, 1625, 1705, 1786, 1870, 1957, 2045, 0, 0, 27, 512, 34816, 4, 2048, 0, 0},
    {21, 75, 164, 241, 318, 394, 470, 549, 626, 705, 781, 860, 919, 998, 1074, 1150, 1228, 1308, 1386, 1468, 1523, 1596, 1670, 1746, 1821, 1897, 1973, 0, 0, 27, 4096, 2048, 2, 34832, 0, 0},
    {22, 97, 176, 256, 337, 417, 496, 555, 628, 706, 782, 861, 941, 1021, 1101, 1151, 1229, 1309, 1371, 1446, 1521, 1598, 1673, 1749, 1824, 1900, 1976, 0, 0, 27, 32768, 2048, 128, 34820, 0, 0},
    {24, 83, 165, 242, 320, 396, 472, 550, 629, 708, 775, 844, 922, 1000, 1077, 1153, 1230, 1310, 1388, 1469, 1531, 1600, 1674, 1750, 1825, 1901, 1977, 0, 0, 27, 1024, 2048, 2, 34832, 0, 0},
    {25, 98, 177, 257, 315, 397, 473, 552, 630, 710, 785, 864, 942, 1024, 1079, 1156, 1233, 1313, 1390, 1472, 1549, 1630, 1710, 1747, 1826, 1904, 1980, 0, 0, 27, 16384, 2048, 16, 34944, 0, 0},
    {26, 100, 178, 258, 340, 421, 500, 563, 632, 712, 788, 866, 945, 1026, 1105, 1186, 1264, 1342, 1407, 1474, 1552, 1633, 1713, 1793, 1876, 1899, 1981, 0, 0, 27, 0, 2052, 128, 35328, 0, 0},
    {28, 101, 180, 260, 341, 422, 502, 580, 658, 707, 789, 869, 948, 1029, 1108, 1159, 1234, 1314, 1393, 1476, 1553, 1595, 1676, 1752, 1828, 1906, 1984, 0, 0, 27, 32768, 2048, 512, 34848, 0, 0},
    {29, 102, 181, 261, 323, 398, 474, 553, 633, 695, 766, 845, 924, 1004, 1081, 1158, 1237, 1291, 1370, 1448, 1522, 1601, 1678, 1754, 1830, 1909, 1986, 0, 0, 27, 512, 2048, 16, 34818, 0, 0},
    {30, 104, 184, 264, 331, 400, 476, 556, 623, 690, 768, 846, 925, 1005, 1067, 1142, 1220, 1296, 1372, 1449, 1524, 1602, 1680, 1756, 1832, 1910, 1989, 0, 0, 27, 256, 2048, 16400, 34816, 0, 0},
    {32, 105, 163, 244, 321, 401, 477, 557, 636, 714, 793, 874, 952, 1032, 1110, 1190, 1266, 1327, 1398, 1481, 1558, 1611, 1681, 1757, 1833, 1912, 1990, 0, 0, 27, 0, 2050, 4, 34848, 0, 0},
    {33, 106, 186, 243, 322, 402, 478, 558, 637, 716, 794, 876, 953, 1033, 1087, 1161, 1240, 1320, 1400, 1443, 1525, 1604, 1682, 1758, 1834, 1913, 1992, 0, 0, 27, 16384, 2048, 8, 34824, 0, 0},
    {34, 108, 188, 268, 348, 429, 508, 585, 664, 742, 817, 896, 973, 1052, 1125, 1204, 1282, 1362, 1438, 1507, 1582, 1631, 1717, 1798, 1881, 1915, 1994, 0, 0, 27, 0, 2080, 0, 35336, 0, 0},
    {36, 91, 166, 245, 324, 404, 471, 536, 613, 692, 769, 848, 928, 1008, 1085, 1164, 1241, 1321, 1402, 1484, 1561, 1638, 1718, 1800, 1843, 1917, 1997, 0, 0, 27, 64, 2048, 2, 35072, 0, 0},
    {37, 109, 189, 269, 349, 403, 481, 561, 640, 718, 797, 877, 943, 1009, 1086, 1165, 1242, 1322, 1404, 1485, 1539, 1606, 1685, 1762, 1838, 1918, 1998, 0, 0, 27, 4096, 2048, 32, 34832, 0, 0},
    {38, 110, 171, 248, 326, 405, 482, 562, 641, 720, 798, 878, 954, 1034, 1112, 1192, 1270, 1346, 1422, 1504, 1559, 1640, 1720, 1755, 1840, 1921, 2001, 0, 0, 27, 0, 2064, 4, 34944, 0, 0},
    {40, 99, 170, 239, 313, 388, 465, 542, 617, 696, 772, 849, 929, 1010, 1088, 1166, 1244, 1324, 1379, 1452, 1528, 1608, 1686, 1764, 1841, 1924, 2004, 0, 0, 27, 8, 2048, 2, 34820, 0, 0},
    {41, 112, 190, 272, 352, 430, 509, 586, 666, 745, 821, 900, 963, 1037, 1114, 1167, 1245, 1325, 1405, 1486, 1565, 1644, 1722, 1805, 1867, 1926, 2006, 0, 0, 27, 32768, 2048, 4096, 35072, 0, 0},
    {42, 113, 193, 274, 354, 433, 512, 588, 643, 724, 802, 882, 958, 1040, 1095, 1168, 1246, 1326, 1387, 1453, 1529, 1609, 1688, 1766, 1844, 1928, 2008, 0, 0, 27, 16384, 2048, 256, 34820, 0, 0},
    {44, 114, 194, 277, 357, 436, 514, 590, 668, 746, 822, 875, 960, 1041, 1117, 1175, 1248, 1299, 1376, 1456, 1532, 1612, 1690, 1769, 1846, 1930, 2010, 0, 0, 27, 32768, 2048, 2048, 34818, 0, 0},
    {45, 116, 179, 249, 328, 406, 485, 565, 645, 726, 805, 885, 951, 1012, 1089, 1170, 1227, 1300, 1377, 1457, 1534, 1614, 1693, 1772, 1849, 1933, 2013, 0, 0, 27, 4096, 2048, 4, 34817, 0, 0},
    {46, 117, 197, 278, 358, 437, 516, 593, 670, 748, 824, 901, 978, 1057, 1132, 1206, 1285, 1339, 1428, 1505, 1585, 1639, 1725, 1808, 1885, 1968, 2019, 0, 0, 27, 0, 2080, 0, 35842, 0, 0},
    {48, 118, 198, 259, 330, 409, 488, 566, 646, 728, 806, 886, 964, 1044, 1111, 1176, 1253, 1307, 1380, 1460, 1537, 1617, 1697, 1776, 1854, 1938, 2018, 0, 0, 27, 16384, 2048, 8, 34818, 0, 0},
    {49, 120, 200, 280, 339, 410, 489, 551, 622, 701, 777, 856, 907, 993, 1069, 1145, 1222, 1302, 1381, 1461, 1540, 1620, 1700, 1778, 1858, 1942, 2022, 0, 0, 27, 128, 2048, 4112, 34816, 0, 0},
    {50, 121, 202, 282, 361, 440, 491, 568, 648, 729, 808, 888, 966, 1045, 1118, 1196, 1276, 1353, 1429, 1506, 1586, 1647, 1730, 1810, 1888, 1931, 2026, 0, 0, 27, 0, 2080, 64, 35328, 0, 0},
    {52, 122, 204, 284, 362, 419, 490, 569, 631, 704, 780, 843, 920, 996, 1072, 1148, 1225, 1305, 1384, 1465, 1544, 1624, 1704, 1782, 1862, 1948, 2030, 0, 0, 27, 256, 2048, 2080, 34816, 0, 0},
    {53, 124, 205, 267, 334, 414, 493, 572, 650, 733, 810, 892, 970, 1049, 1122, 1201, 1280, 1360, 1423, 1497, 1578, 1660, 1740, 1818, 1896, 1972, 2043, 0, 0, 27, 0, 2052, 8, 35840, 0, 0},
    {54, 125, 206, 285, 364, 442, 499, 573, 652, 734, 812, 863, 938, 1020, 1100, 1182, 1260, 1340, 1417, 1467, 1546, 1626, 1706, 1788, 1872, 1958, 2046, 0, 0, 27, 2048, 2048, 64, 34824, 0, 0},
    {56, 126, 187, 254, 336, 416, 494, 574, 653, 736, 813, 871, 940, 995, 1076, 1152, 1215, 1294, 1369, 1445, 1520, 1597, 1672, 1748, 1822, 1898, 1974, 0, 0, 27, 2048, 34817, 8196, 2048, 0, 0},
    {57, 128, 208, 286, 365, 444, 521, 579, 654, 737, 814, 893, 959, 1022, 1102, 1184, 1261, 1341, 1418, 1498, 1547, 1628, 1708, 1789, 1873, 1960, 1975, 0, 0, 27, 4096, 35840, 128, 2064, 0, 0},
    {58, 129, 209, 275, 338, 418, 497, 576, 639, 709, 784, 862, 923, 1001, 1078, 1154, 1232, 1312, 1389, 1470, 1548, 1629, 1709, 1790, 1831, 1902, 1978, 0, 0, 27, 256, 35072, 4104, 2048, 0, 0},
    {60, 130, 210, 288, 347, 420, 498, 577, 656, 703, 786, 865, 944, 1025, 1104, 1185, 1262, 1315, 1392, 1473, 1550, 1632, 1712, 1792, 1874, 1961, 1983, 0, 0, 27, 512, 35840, 16, 2050, 0, 0},
    {61, 132, 212, 289, 366, 427, 501, 578, 657, 738, 799, 868, 946, 1028, 1106, 1188, 1265, 1344, 1420, 1500, 1580, 1661, 1707, 1794, 1839, 1905, 1982, 0, 0, 27, 1024, 35072, 32, 2112, 0, 0},
    {62, 133, 213, 290, 355, 424, 504, 581, 660, 740, 807, 870, 931, 1002, 1080, 1157, 1236, 1316, 1394, 1477, 1554, 1607, 1677, 1753, 1829, 1908, 1985, 0, 0, 27, 1024, 34848, 4112, 2048, 0, 0},
    {64, 107, 182, 262, 342, 425, 487, 554, 634, 713, 790, 872, 949, 1030, 1109, 1189, 1243, 1317, 1396, 1478, 1556, 1634, 1714, 1796, 1877, 1911, 1988, 0, 0, 27, 64, 35328, 2, 2049, 0, 0},
    {65, 134, 214, 283, 344, 426, 505, 582, 661, 719, 792, 873, 950, 1003, 1082, 1160, 1238, 1318, 1397, 1480, 1557, 1636, 1716, 1797, 1878, 1962, 1991, 0, 0, 27, 512, 35840, 8200, 2048, 0, 0},
    {66, 115, 185, 265, 345, 428, 506, 584, 662, 741, 816, 894, 972, 1050, 1124, 1202, 1281, 1361, 1431, 1501, 1581, 1662, 1741, 1803, 1880, 1964, 1999, 0, 0, 27, 0, 35844, 2, 2176, 0, 0},
    {68, 136, 195, 266, 346, 399, 480, 560, 638, 717, 796, 851, 926, 1006, 1084, 1162, 1223, 1297, 1373, 1450, 1526, 1605, 1684, 1760, 1836, 1914, 1993, 0, 0, 27, 32, 34817, 2052, 2048, 0, 0},
    {69, 137, 216, 292, 368, 445, 522, 600, 676, 753, 829, 899, 974, 1053, 1126, 1183, 1268, 1331, 1401, 1482, 1560, 1637, 1679, 1761, 1837, 1916, 1996, 0, 0, 27, 32768, 34880, 2048, 2050, 0, 0},
    {70, 138, 217, 293, 369, 446, 524, 587, 665, 744, 818, 897, 976, 1054, 1128, 1205, 1284, 1364, 1440, 1516, 1591, 1664, 1715, 1801, 1882, 1965, 2007, 0, 0, 27, 0, 35856, 128, 2112, 0, 0},
    {72, 140, 218, 294, 370, 448, 525, 601, 677, 731, 820, 898, 977, 1056, 1129, 1191, 1269, 1345, 1421, 1502, 1584, 1665, 1723, 1802, 1855, 1920, 2000, 0, 0, 27, 32768, 35072, 512, 2112, 0, 0},
    {73, 141, 203, 270, 350, 415, 484, 564, 642, 721, 800, 880, 956, 1036, 1113, 1193, 1272, 1348, 1424, 1475, 1562, 1641, 1721, 1804, 1863, 1922, 2002, 0, 0, 27, 32, 35072, 4, 2056, 0, 0},
    {74, 142, 220, 296, 372, 449, 526, 602, 678, 754, 830, 906, 984, 1027, 1130, 1199, 1273, 1349, 1425, 1483, 1564, 1642, 1687, 1765, 1842, 1925, 2005, 0, 0, 27, 32768, 34880, 8192, 2056, 0, 0},
    {76, 123, 192, 273, 353, 432, 510, 575, 644, 722, 801, 881, 957, 1038, 1116, 1194, 1274, 1350, 1426, 1491, 1566, 1645, 1724, 1806, 1884, 1966, 2015, 0, 0, 27, 128, 35840, 2, 2056, 0, 0},
    {77, 144, 211, 276, 356, 434, 513, 589, 655, 725, 779, 850, 930, 991, 1068, 1144, 1221, 1298, 1374, 1454, 1530, 1610, 1689, 1768, 1845, 1929, 2009, 0, 0, 27, 8448, 34816, 1028, 2048, 0, 0},
    {78, 145, 221, 297, 373, 450, 507, 592, 669, 727, 804, 884, 961, 1042, 1099, 1169, 1249, 1328, 1406, 1455, 1533, 1613, 1692, 1770, 1848, 1932, 2012, 0, 0, 27, 512, 34824, 16448, 2048, 0, 0},
    {80, 131, 196, 255, 329, 408, 486, 539, 618, 697, 773, 852, 932, 1013, 1090, 1172, 1239, 1301, 1378, 1458, 1536, 1616, 1694, 1773, 1850, 1934, 2014, 0, 0, 27, 8, 34817, 130, 2048, 0, 0},
    {81, 146, 222, 298, 374, 452, 515, 594, 672, 749, 825, 887, 962, 1011, 1092, 1173, 1250, 1329, 1408, 1488, 1568, 1646, 1726, 1767, 1852, 1936, 2016, 0, 0, 27, 2048, 34944, 8256, 2048, 0, 0},
    {82, 148, 224, 300, 376, 453, 528, 604, 680, 739, 826, 895, 965, 1019, 1094, 1177, 1254, 1332, 1410, 1490, 1570, 1648, 1728, 1775, 1856, 1940, 2020, 0, 0, 27, 2048, 34944, 8704, 2048, 0, 0},
    {84, 139, 201, 281, 360, 438, 517, 596, 673, 750, 828, 902, 980, 1058, 1133, 1208, 1271, 1352, 1411, 1492, 1572, 1649, 1729, 1809, 1886, 1927, 2024, 0, 0, 27, 0, 35329, 2, 2052, 0, 0},
    {85, 149, 225, 301, 377, 435, 518, 597, 663, 730, 787, 858, 937, 1018, 1098, 1181, 1258, 1336, 1413, 1493, 1573, 1650, 1732, 1812, 1879, 1945, 2028, 0, 0, 27, 256, 35072, 1056, 2048, 0, 0},
    {86, 150, 226, 302, 363, 441, 520, 598, 674, 752, 815, 889, 968, 1046, 1120, 1198, 1251, 1337, 1414, 1494, 1576, 1657, 1703, 1785, 1869, 1956, 2042, 0, 0, 27, 1024, 34880, 16, 2049, 0, 0},
};

__device__ __forceinline__ uint32_t smem_u32(const void* p) { return (uint32_t)__cvta_generic_to_shared(p); }
__device__ __forceinline__ void mbar_init(uint32_t bar, uint32_t cnt) {
    asm volatile("mbarrier.init.shared::cta.b64 [%0], %1;" ::"r"(bar), "r"(cnt));
}
__device__ __forceinline__ void mbar_expect_tx(uint32_t bar, uint32_t bytes) {
    asm volatile("mbarrier.arrive.expect_tx.shared::cta.b64 _, [%0], %1;" ::"r"(bar), "r"(bytes) : "memory");
}
__device__ __forceinline__ void mbar_arrive(uint32_t bar) {
    asm volatile("mbarrier.arrive.shared::cta.b64 _, [%0];" ::"r"(bar) : "memory");
}
__device__ __forceinline__ void mbar_arrive_cluster_pred(uint32_t addr, uint32_t pred) {
    asm volatile(
        "{\n.reg .pred p;\n"
        "setp.ne.u32 p, %1, 0;\n"
        "@p mbarrier.arrive.shared::cluster.b64 _, [%0];\n}\n" ::"r"(addr), "r"(pred) : "memory");
}
__device__ __forceinline__ void mbar_arrive_pred(uint32_t addr, uint32_t pred) {
    asm volatile(
        "{\n.reg .pred p;\n"
        "setp.ne.u32 p, %1, 0;\n"
        "@p mbarrier.arrive.shared::cta.b64 _, [%0];\n}\n" ::"r"(addr), "r"(pred) : "memory");
}
__device__ __forceinline__ uint32_t mapa(uint32_t addr, uint32_t cta) {
    uint32_t r;
    asm("mapa.shared::cluster.u32 %0, %1, %2;" : "=r"(r) : "r"(addr), "r"(cta));
    return r;
}
__device__ __forceinline__ void mbar_wait(uint32_t bar, uint32_t parity) {
    asm volatile(
        "{\n.reg .pred p;\n"
        "WAIT_LOOP:\n"
        "mbarrier.try_wait.parity.shared::cta.b64 p, [%0], %1;\n"
        "@p bra WAIT_DONE;\n"
        "bra WAIT_LOOP;\n"
        "WAIT_DONE:\n}\n" ::"r"(bar), "r"(parity) : "memory");
}
__device__ __forceinline__ bool elect_one() {
    uint32_t pred;
    asm volatile("{\n.reg .pred p;\nelect.sync _|p, 0xffffffff;\nselp.u32 %0, 1, 0, p;\n}\n" : "=r"(pred));
    return pred != 0;
}
__device__ __forceinline__ void tma_load_kv(uint32_t dst, const CUtensorMap* tm, int g, uint32_t bar) {
    asm volatile(
        "cp.async.bulk.tensor.4d.shared::cluster.global.mbarrier::complete_tx::bytes [%0], [%1, {%3, %3, %3, %4}], [%2];" ::"r"(dst),
        "l"(tm), "r"(bar), "r"(0), "r"(g)
        : "memory");
}
__device__ __forceinline__ void tma_load_kv_mc(uint32_t dst, const CUtensorMap* tm, int g, uint32_t bar) {
    asm volatile(
        "cp.async.bulk.tensor.4d.shared::cluster.global.mbarrier::complete_tx::bytes.multicast::cluster [%0], [%1, {%3, %3, %3, %4}], [%2], %5;" ::"r"(dst),
        "l"(tm), "r"(bar), "r"(0), "r"(g), "h"((uint16_t)3)
        : "memory");
}
__device__ __forceinline__ void tma_load_q(uint32_t dst, const CUtensorMap* tm, int g, int head, uint32_t bar) {
    asm volatile(
        "cp.async.bulk.tensor.5d.shared::cluster.global.mbarrier::complete_tx::bytes [%0], [%1, {%3, %3, %3, %4, %5}], [%2];" ::"r"(dst),
        "l"(tm), "r"(bar), "r"(0), "r"(g), "r"(head)
        : "memory");
}
__device__ __forceinline__ void tma_store_o(const CUtensorMap* tm, uint32_t src, int g, int head) {
    asm volatile("cp.async.bulk.tensor.5d.global.shared::cta.bulk_group [%0, {%2, %2, %2, %3, %4}], [%1];" ::"l"(tm),
                 "r"(src), "r"(0), "r"(g), "r"(head)
                 : "memory");
}
__device__ __forceinline__ void bulk_commit() { asm volatile("cp.async.bulk.commit_group;" ::: "memory"); }
__device__ __forceinline__ void bulk_wait_read() { asm volatile("cp.async.bulk.wait_group.read 0;" ::: "memory"); }
__device__ __forceinline__ void fence_async_smem() { asm volatile("fence.proxy.async.shared::cta;" ::: "memory"); }
__device__ __forceinline__ void stsm_x4(uint32_t addr, uint32_t r0, uint32_t r1, uint32_t r2, uint32_t r3) {
    asm volatile("stmatrix.sync.aligned.m8n8.x4.shared.b16 [%0], {%1, %2, %3, %4};" ::"r"(addr), "r"(r0), "r"(r1), "r"(r2), "r"(r3) : "memory");
}
__device__ __forceinline__ void ldsm_x4(uint32_t addr, uint32_t& r0, uint32_t& r1, uint32_t& r2, uint32_t& r3) {
    asm volatile("ldmatrix.sync.aligned.m8n8.x4.shared.b16 {%0, %1, %2, %3}, [%4];" : "=r"(r0), "=r"(r1), "=r"(r2), "=r"(r3) : "r"(addr) : "memory");
}
__device__ __forceinline__ void wgmma_fence() { asm volatile("wgmma.fence.sync.aligned;" ::: "memory"); }
__device__ __forceinline__ void wgmma_commit() { asm volatile("wgmma.commit_group.sync.aligned;" ::: "memory"); }
template <int N>
__device__ __forceinline__ void wgmma_wait() { asm volatile("wgmma.wait_group.sync.aligned %0;" ::"n"(N) : "memory"); }
__device__ __forceinline__ void bar_sync(int id, int n) { asm volatile("bar.sync %0, %1;" ::"r"(id), "r"(n) : "memory"); }
__device__ __forceinline__ void bar_arrive(int id, int n) { asm volatile("bar.arrive %0, %1;" ::"r"(id), "r"(n) : "memory"); }
__device__ __forceinline__ float ex2(float x) {
    float y;
    asm("ex2.approx.ftz.f32 %0, %1;" : "=f"(y) : "f"(x));
    return y;
}
__device__ __forceinline__ uint32_t pack_bf16(float lo, float hi) {
    uint32_t r;
    asm("cvt.rn.bf16x2.f32 %0, %1, %2;" : "=r"(r) : "f"(hi), "f"(lo));
    return r;
}
template <int N>
__device__ __forceinline__ void fence_regs(float (&r)[N]) {
#pragma unroll
    for (int i = 0; i < N; i++) asm volatile("" : "+f"(r[i])::"memory");
}
template <int N>
__device__ __forceinline__ void fence_regs(uint32_t (&r)[N]) {
#pragma unroll
    for (int i = 0; i < N; i++) asm volatile("" : "+r"(r[i])::"memory");
}
template <int N>
__device__ __forceinline__ void forget(float (&r)[N]) {
#pragma unroll
    for (int i = 0; i < N; i++) r[i] = 0.f;
}
__device__ __forceinline__ void fence_regs2(float& a, float& b) { asm volatile("" : "+f"(a), "+f"(b)::"memory"); }
__device__ __forceinline__ uint64_t make_desc(uint32_t lo, uint32_t hi) { return ((uint64_t)hi << 32) | lo; }
constexpr uint32_t DESC_HI = (GRP_BYTES >> 4) | (1u << 30);

__device__ __forceinline__ void wgmma_qk(float (&d)[32], uint32_t a0, uint32_t a1, uint32_t a2, uint32_t a3, uint64_t descB) {
    asm volatile(
        "{\n.reg .pred p;\n"
        "setp.eq.b32 p, 0, 0;\n"
        "wgmma.mma_async.sync.aligned.m64n64k16.f32.bf16.bf16 "
        "{%0, %1, %2, %3, %4, %5, %6, %7, %8, %9, %10, %11, %12, %13, %14, %15, "
        "%16, %17, %18, %19, %20, %21, %22, %23, %24, %25, %26, %27, %28, %29, %30, %31}, "
        "{%32, %33, %34, %35}, %36, p, 1, 1, 0;\n}\n"
        : "+f"(d[0]), "+f"(d[1]), "+f"(d[2]), "+f"(d[3]), "+f"(d[4]), "+f"(d[5]), "+f"(d[6]), "+f"(d[7]),
          "+f"(d[8]), "+f"(d[9]), "+f"(d[10]), "+f"(d[11]), "+f"(d[12]), "+f"(d[13]), "+f"(d[14]), "+f"(d[15]),
          "+f"(d[16]), "+f"(d[17]), "+f"(d[18]), "+f"(d[19]), "+f"(d[20]), "+f"(d[21]), "+f"(d[22]), "+f"(d[23]),
          "+f"(d[24]), "+f"(d[25]), "+f"(d[26]), "+f"(d[27]), "+f"(d[28]), "+f"(d[29]), "+f"(d[30]), "+f"(d[31])
        : "r"(a0), "r"(a1), "r"(a2), "r"(a3), "l"(descB));
}

__device__ __forceinline__ void wgmma_qk_init(float (&d)[32], uint32_t a0, uint32_t a1, uint32_t a2, uint32_t a3, uint64_t descB) {
    asm volatile(
        "{\n.reg .pred p;\n"
        "setp.ne.b32 p, 0, 0;\n"
        "wgmma.mma_async.sync.aligned.m64n64k16.f32.bf16.bf16 "
        "{%0, %1, %2, %3, %4, %5, %6, %7, %8, %9, %10, %11, %12, %13, %14, %15, "
        "%16, %17, %18, %19, %20, %21, %22, %23, %24, %25, %26, %27, %28, %29, %30, %31}, "
        "{%32, %33, %34, %35}, %36, p, 1, 1, 0;\n}\n"
        : "=f"(d[0]), "=f"(d[1]), "=f"(d[2]), "=f"(d[3]), "=f"(d[4]), "=f"(d[5]), "=f"(d[6]), "=f"(d[7]),
          "=f"(d[8]), "=f"(d[9]), "=f"(d[10]), "=f"(d[11]), "=f"(d[12]), "=f"(d[13]), "=f"(d[14]), "=f"(d[15]),
          "=f"(d[16]), "=f"(d[17]), "=f"(d[18]), "=f"(d[19]), "=f"(d[20]), "=f"(d[21]), "=f"(d[22]), "=f"(d[23]),
          "=f"(d[24]), "=f"(d[25]), "=f"(d[26]), "=f"(d[27]), "=f"(d[28]), "=f"(d[29]), "=f"(d[30]), "=f"(d[31])
        : "r"(a0), "r"(a1), "r"(a2), "r"(a3), "l"(descB));
}

__device__ __forceinline__ void wgmma_pv(float (&d)[96], uint32_t a0, uint32_t a1, uint32_t a2, uint32_t a3, uint64_t descB) {
    asm volatile(
        "{\n.reg .pred p;\n"
        "setp.eq.b32 p, 0, 0;\n"
        "wgmma.mma_async.sync.aligned.m64n192k16.f32.bf16.bf16 "
        "{%0, %1, %2, %3, %4, %5, %6, %7, %8, %9, %10, %11, %12, %13, %14, %15, "
        "%16, %17, %18, %19, %20, %21, %22, %23, %24, %25, %26, %27, %28, %29, %30, %31, "
        "%32, %33, %34, %35, %36, %37, %38, %39, %40, %41, %42, %43, %44, %45, %46, %47, "
        "%48, %49, %50, %51, %52, %53, %54, %55, %56, %57, %58, %59, %60, %61, %62, %63, "
        "%64, %65, %66, %67, %68, %69, %70, %71, %72, %73, %74, %75, %76, %77, %78, %79, "
        "%80, %81, %82, %83, %84, %85, %86, %87, %88, %89, %90, %91, %92, %93, %94, %95}, "
        "{%96, %97, %98, %99}, %100, p, 1, 1, 1;\n}\n"
        : "+f"(d[0]), "+f"(d[1]), "+f"(d[2]), "+f"(d[3]), "+f"(d[4]), "+f"(d[5]), "+f"(d[6]), "+f"(d[7]),
          "+f"(d[8]), "+f"(d[9]), "+f"(d[10]), "+f"(d[11]), "+f"(d[12]), "+f"(d[13]), "+f"(d[14]), "+f"(d[15]),
          "+f"(d[16]), "+f"(d[17]), "+f"(d[18]), "+f"(d[19]), "+f"(d[20]), "+f"(d[21]), "+f"(d[22]), "+f"(d[23]),
          "+f"(d[24]), "+f"(d[25]), "+f"(d[26]), "+f"(d[27]), "+f"(d[28]), "+f"(d[29]), "+f"(d[30]), "+f"(d[31]),
          "+f"(d[32]), "+f"(d[33]), "+f"(d[34]), "+f"(d[35]), "+f"(d[36]), "+f"(d[37]), "+f"(d[38]), "+f"(d[39]),
          "+f"(d[40]), "+f"(d[41]), "+f"(d[42]), "+f"(d[43]), "+f"(d[44]), "+f"(d[45]), "+f"(d[46]), "+f"(d[47]),
          "+f"(d[48]), "+f"(d[49]), "+f"(d[50]), "+f"(d[51]), "+f"(d[52]), "+f"(d[53]), "+f"(d[54]), "+f"(d[55]),
          "+f"(d[56]), "+f"(d[57]), "+f"(d[58]), "+f"(d[59]), "+f"(d[60]), "+f"(d[61]), "+f"(d[62]), "+f"(d[63]),
          "+f"(d[64]), "+f"(d[65]), "+f"(d[66]), "+f"(d[67]), "+f"(d[68]), "+f"(d[69]), "+f"(d[70]), "+f"(d[71]),
          "+f"(d[72]), "+f"(d[73]), "+f"(d[74]), "+f"(d[75]), "+f"(d[76]), "+f"(d[77]), "+f"(d[78]), "+f"(d[79]),
          "+f"(d[80]), "+f"(d[81]), "+f"(d[82]), "+f"(d[83]), "+f"(d[84]), "+f"(d[85]), "+f"(d[86]), "+f"(d[87]),
          "+f"(d[88]), "+f"(d[89]), "+f"(d[90]), "+f"(d[91]), "+f"(d[92]), "+f"(d[93]), "+f"(d[94]), "+f"(d[95])
        : "r"(a0), "r"(a1), "r"(a2), "r"(a3), "l"(descB));
}

__device__ __forceinline__ void wgmma_pv_init(float (&d)[96], uint32_t a0, uint32_t a1, uint32_t a2, uint32_t a3, uint64_t descB) {
    asm volatile(
        "{\n.reg .pred p;\n"
        "setp.ne.b32 p, 0, 0;\n"
        "wgmma.mma_async.sync.aligned.m64n192k16.f32.bf16.bf16 "
        "{%0, %1, %2, %3, %4, %5, %6, %7, %8, %9, %10, %11, %12, %13, %14, %15, "
        "%16, %17, %18, %19, %20, %21, %22, %23, %24, %25, %26, %27, %28, %29, %30, %31, "
        "%32, %33, %34, %35, %36, %37, %38, %39, %40, %41, %42, %43, %44, %45, %46, %47, "
        "%48, %49, %50, %51, %52, %53, %54, %55, %56, %57, %58, %59, %60, %61, %62, %63, "
        "%64, %65, %66, %67, %68, %69, %70, %71, %72, %73, %74, %75, %76, %77, %78, %79, "
        "%80, %81, %82, %83, %84, %85, %86, %87, %88, %89, %90, %91, %92, %93, %94, %95}, "
        "{%96, %97, %98, %99}, %100, p, 1, 1, 1;\n}\n"
        : "=f"(d[0]), "=f"(d[1]), "=f"(d[2]), "=f"(d[3]), "=f"(d[4]), "=f"(d[5]), "=f"(d[6]), "=f"(d[7]),
          "=f"(d[8]), "=f"(d[9]), "=f"(d[10]), "=f"(d[11]), "=f"(d[12]), "=f"(d[13]), "=f"(d[14]), "=f"(d[15]),
          "=f"(d[16]), "=f"(d[17]), "=f"(d[18]), "=f"(d[19]), "=f"(d[20]), "=f"(d[21]), "=f"(d[22]), "=f"(d[23]),
          "=f"(d[24]), "=f"(d[25]), "=f"(d[26]), "=f"(d[27]), "=f"(d[28]), "=f"(d[29]), "=f"(d[30]), "=f"(d[31]),
          "=f"(d[32]), "=f"(d[33]), "=f"(d[34]), "=f"(d[35]), "=f"(d[36]), "=f"(d[37]), "=f"(d[38]), "=f"(d[39]),
          "=f"(d[40]), "=f"(d[41]), "=f"(d[42]), "=f"(d[43]), "=f"(d[44]), "=f"(d[45]), "=f"(d[46]), "=f"(d[47]),
          "=f"(d[48]), "=f"(d[49]), "=f"(d[50]), "=f"(d[51]), "=f"(d[52]), "=f"(d[53]), "=f"(d[54]), "=f"(d[55]),
          "=f"(d[56]), "=f"(d[57]), "=f"(d[58]), "=f"(d[59]), "=f"(d[60]), "=f"(d[61]), "=f"(d[62]), "=f"(d[63]),
          "=f"(d[64]), "=f"(d[65]), "=f"(d[66]), "=f"(d[67]), "=f"(d[68]), "=f"(d[69]), "=f"(d[70]), "=f"(d[71]),
          "=f"(d[72]), "=f"(d[73]), "=f"(d[74]), "=f"(d[75]), "=f"(d[76]), "=f"(d[77]), "=f"(d[78]), "=f"(d[79]),
          "=f"(d[80]), "=f"(d[81]), "=f"(d[82]), "=f"(d[83]), "=f"(d[84]), "=f"(d[85]), "=f"(d[86]), "=f"(d[87]),
          "=f"(d[88]), "=f"(d[89]), "=f"(d[90]), "=f"(d[91]), "=f"(d[92]), "=f"(d[93]), "=f"(d[94]), "=f"(d[95])
        : "r"(a0), "r"(a1), "r"(a2), "r"(a3), "l"(descB));
}

__device__ __forceinline__ void wgmma_rk(float (&d)[8], uint64_t descA, uint64_t descB) {
    asm volatile(
        "{\n.reg .pred p;\n"
        "setp.eq.b32 p, 0, 0;\n"
        "wgmma.mma_async.sync.aligned.m64n16k16.f32.bf16.bf16 "
        "{%0, %1, %2, %3, %4, %5, %6, %7}, "
        "%8, %9, p, 1, 1, 0, 0;\n}\n"
        : "+f"(d[0]), "+f"(d[1]), "+f"(d[2]), "+f"(d[3]), "+f"(d[4]), "+f"(d[5]), "+f"(d[6]), "+f"(d[7])
        : "l"(descA), "l"(descB));
}

__device__ __forceinline__ void wgmma_rk_init(float (&d)[8], uint64_t descA, uint64_t descB) {
    asm volatile(
        "{\n.reg .pred p;\n"
        "setp.ne.b32 p, 0, 0;\n"
        "wgmma.mma_async.sync.aligned.m64n16k16.f32.bf16.bf16 "
        "{%0, %1, %2, %3, %4, %5, %6, %7}, "
        "%8, %9, p, 1, 1, 0, 0;\n}\n"
        : "=f"(d[0]), "=f"(d[1]), "=f"(d[2]), "=f"(d[3]), "=f"(d[4]), "=f"(d[5]), "=f"(d[6]), "=f"(d[7])
        : "l"(descA), "l"(descB));
}

__device__ __forceinline__ void wgmma_rv(float (&d)[8], uint64_t descA, uint64_t descB) {
    asm volatile(
        "{\n.reg .pred p;\n"
        "setp.eq.b32 p, 0, 0;\n"
        "wgmma.mma_async.sync.aligned.m64n16k16.f32.bf16.bf16 "
        "{%0, %1, %2, %3, %4, %5, %6, %7}, "
        "%8, %9, p, 1, 1, 1, 0;\n}\n"
        : "+f"(d[0]), "+f"(d[1]), "+f"(d[2]), "+f"(d[3]), "+f"(d[4]), "+f"(d[5]), "+f"(d[6]), "+f"(d[7])
        : "l"(descA), "l"(descB));
}

__device__ __forceinline__ void wgmma_rl(float (&d)[8], uint32_t a0, uint32_t a1, uint32_t a2, uint32_t a3, uint64_t descB) {
    asm volatile(
        "{\n.reg .pred p;\n"
        "setp.eq.b32 p, 0, 0;\n"
        "wgmma.mma_async.sync.aligned.m64n16k16.f32.bf16.bf16 "
        "{%0, %1, %2, %3, %4, %5, %6, %7}, "
        "{%8, %9, %10, %11}, %12, p, 1, 1, 0;\n}\n"
        : "+f"(d[0]), "+f"(d[1]), "+f"(d[2]), "+f"(d[3]), "+f"(d[4]), "+f"(d[5]), "+f"(d[6]), "+f"(d[7])
        : "r"(a0), "r"(a1), "r"(a2), "r"(a3), "l"(descB));
}

__device__ __forceinline__ void wgmma_rl_init(float (&d)[8], uint32_t a0, uint32_t a1, uint32_t a2, uint32_t a3, uint64_t descB) {
    asm volatile(
        "{\n.reg .pred p;\n"
        "setp.ne.b32 p, 0, 0;\n"
        "wgmma.mma_async.sync.aligned.m64n16k16.f32.bf16.bf16 "
        "{%0, %1, %2, %3, %4, %5, %6, %7}, "
        "{%8, %9, %10, %11}, %12, p, 1, 1, 0;\n}\n"
        : "=f"(d[0]), "=f"(d[1]), "=f"(d[2]), "=f"(d[3]), "=f"(d[4]), "=f"(d[5]), "=f"(d[6]), "=f"(d[7])
        : "r"(a0), "r"(a1), "r"(a2), "r"(a3), "l"(descB));
}


struct Item { int head; int grp; bool mc, rem; };
__device__ __forceinline__ Item decode_item(uint32_t e, int rank, int w) {
    Item it;
    it.mc = (e & 3) != 3;
    it.rem = !it.mc && (e >> 2 & 1) != w;
    it.head = it.mc ? e >> 2 : (e >> 3) * 2 + rank;
    it.grp = 32 * (e & 3) + (it.mc ? 16 * rank + 8 * w : it.rem ? 8 : 0);
    return it;
}
__device__ __forceinline__ uint32_t first_entry(uint32_t c) { return (c / 3) * 4 + c % 3; }

__device__ __forceinline__ uint32_t k_addr(int e) { return SM_K + ((e + KROT) & 3) * BLK_BYTES; }
__device__ __forceinline__ void next_v(uint32_t& v) { v = v == SM_V + 2 * BLK_BYTES ? SM_V : v + BLK_BYTES; }
__device__ __forceinline__ void wait_blocks(uint32_t sbase, int e) { mbar_wait(sbase + BAR_FULL + 8 * (e & 3), e >> 2 & 1); }
__device__ __forceinline__ uint64_t k_desc(int e) {
    return make_desc(((e + KROT) & 3) * (BLK_BYTES >> 4) + (((SM_BASE + SM_K) >> 4) | (1u << 16)), DESC_HI);
}
constexpr uint32_t V_DESC0 = ((SM_BASE + SM_V) >> 4) | ((SLAB_BYTES >> 4) << 16);
__device__ __forceinline__ void next_v_desc(uint32_t& v) { v = v == V_DESC0 + 2 * (BLK_BYTES >> 4) ? V_DESC0 : v + (BLK_BYTES >> 4); }
__device__ __forceinline__ constexpr uint32_t k_step(int k) { return (k & 3) == 3 ? (SLAB_BYTES >> 4) - 6 : 2; }

template <bool SPLIT>
__device__ __forceinline__ void issue_qk(float (&s)[32], uint32_t (&q)[48], int e) {
    fence_regs(q);
    wgmma_fence();
    uint64_t desc = k_desc(e);
#pragma unroll
    for (int k = 0; k < 12; k++) {
        if (k == 0) wgmma_qk_init(s, q[0], q[1], q[2], q[3], desc);
        else wgmma_qk(s, q[4 * k], q[4 * k + 1], q[4 * k + 2], q[4 * k + 3], desc);
        if (k < 11) desc += k_step(k);
        if (SPLIT && (k & 3) == 3) wgmma_commit();
    }
    if (!SPLIT) wgmma_commit();
}
template <bool FIRST, bool WAIT = true, bool FENCE = true>
__device__ __forceinline__ void issue_pv(float (&o)[96], uint32_t (&p)[16], uint32_t sbase, int b, uint32_t& v) {
    if (WAIT) wait_blocks(sbase, b + 2);
    if (!FIRST) fence_regs(o);
    fence_regs(p);
    if (FENCE) wgmma_fence();
    uint64_t desc = make_desc(v, DESC_HI);
#pragma unroll
    for (int k = 0; k < 4; k++) {
        if (FIRST && k == 0) wgmma_pv_init(o, p[0], p[1], p[2], p[3], desc);
        else wgmma_pv(o, p[4 * k], p[4 * k + 1], p[4 * k + 2], p[4 * k + 3], desc);
        if (k < 3) desc += 2 * GRP_BYTES >> 4;
    }
    wgmma_commit();
    next_v_desc(v);
}

__device__ __forceinline__ float opaque_copy(float x, uint32_t zero) { return x + __uint_as_float(zero); }

__device__ __forceinline__ float after(float x, float y, uint32_t zero) { return __uint_as_float(__float_as_uint(x) | (__float_as_uint(y) & zero)); }

template <bool FIRST, int LO, int HI>
__device__ __forceinline__ void exp_range(float (&s)[32], float (&l)[2]) {
#pragma unroll
    for (int i = LO; i < HI; i++) s[i] = ex2(s[i]);
#pragma unroll
    for (int i = LO / 4; i < HI / 4; i++) {
        const float x = s[4 * i] + s[4 * i + 1], y = s[4 * i + 2] + s[4 * i + 3];
        if (FIRST && i == LO / 4) { l[0] = x; l[1] = y; }
        else { l[0] += x; l[1] += y; }
    }
}
__device__ __forceinline__ void pack_p(const float (&s)[32], uint32_t (&p)[16]) {
#pragma unroll
    for (int i = 0; i < 8; i++) {
        p[2 * i] = pack_bf16(s[4 * i], s[4 * i + 1]);
        p[2 * i + 1] = pack_bf16(s[4 * i + 2], s[4 * i + 3]);
    }
}
__device__ __forceinline__ bool sum_unsafe(float l) { return __float_as_uint(l) - SUM_LOW > SUM_HIGH - SUM_LOW; }

__device__ __forceinline__ void bb_boundary(uint32_t zero, float& x, float& y) {
    if (zero) {
#pragma unroll
        for (int i = 0; i < 12; i++) {
            asm volatile("mul.f32 %0, %0, %1;" : "+f"(x) : "f"(y));
            asm volatile("mul.f32 %0, %0, %1;" : "+f"(y) : "f"(x));
        }
    }
}
__device__ __forceinline__ void bb_boundary(uint32_t zero, float (&x)[2][2]) {
    if (zero) {
#pragma unroll
        for (int i = 0; i < 24; i++) asm volatile("mul.f32 %0, %0, %1;" : "+f"(x[i >> 1 & 1][i & 1]) : "f"(x[~i >> 1 & 1][i & 1]));
    }
}
__device__ __forceinline__ void bb_boundary(uint32_t zero, float (&x)[4]) {
    if (zero) {
#pragma unroll
        for (int i = 0; i < 24; i++) asm volatile("mul.f32 %0, %0, %1;" : "+f"(x[i & 3]) : "f"(x[(i + 2) & 3]));
    }
}
template <int CB>
__device__ __forceinline__ void load_q_slab(uint32_t (&q)[48], const uint32_t (&q_lane)[4]) {
#pragma unroll
    for (int k = 4 * CB; k < 4 * CB + 4; k++)
        ldsm_x4(q_lane[k & 3] + CB * SLAB_BYTES, q[4 * k], q[4 * k + 1], q[4 * k + 2], q[4 * k + 3]);
}
template <int LO, int HI>
__device__ __forceinline__ void scale_q(uint32_t (&q)[48]) {
#pragma unroll
    for (int i = LO; i < HI; i++)
        asm("{\n.reg .b32 t;\nmul.rn.bf16x2 t, %0, %1;\nfma.rn.bf16x2 %0, %0, %2, t;\n}\n" : "+r"(q[i]) : "r"(SCALE_LO), "r"(SCALE_HI));
}
__device__ __forceinline__ void row_normalisers(float l0, float l1, float (&inv)[2][2], uint32_t& redo, uint32_t bit, uint32_t zero) {
    l0 += __shfl_xor_sync(0xffffffffu, l0, 1);
    l1 += __shfl_xor_sync(0xffffffffu, l1, 1);
    l0 += __shfl_xor_sync(0xffffffffu, l0, 2);
    l1 += __shfl_xor_sync(0xffffffffu, l1, 2);
    asm("rcp.approx.ftz.f32 %0, %1;" : "=f"(inv[0][0]) : "f"(l0));
    asm("rcp.approx.ftz.f32 %0, %1;" : "=f"(inv[1][0]) : "f"(l1));
    inv[0][1] = opaque_copy(inv[0][0], zero);
    inv[1][1] = opaque_copy(inv[1][0], zero);
    if (sum_unsafe(l0) | sum_unsafe(l1)) redo |= bit;
}
__device__ __forceinline__ void cvt_out(float (&o)[96], int k, const float (&inv)[2][2], uint32_t (&x)[4]) {
    float y[8];
#pragma unroll
    for (int i = 0; i < 8; i++) y[i] = o[8 * k + i] * inv[i >> 1 & 1][i & 1];
#pragma unroll
    for (int i = 0; i < 4; i++) x[i] = pack_bf16(y[2 * i], y[2 * i + 1]);
}
template <int K0, int K1, bool GAPS>
__device__ __forceinline__ void stage_output(float (&o)[96], const float (&inv)[2][2], const uint32_t (&q_lane)[4]) {
#pragma unroll
    for (int k = K0; k < K1; k++) {
        uint32_t x[4];
        cvt_out(o, k, inv, x);
        if (GAPS && (GAPW >> (k & 1) & 1)) wgmma_wait<0>();
        stsm_x4(q_lane[k & 3] + (k >> 2) * SLAB_BYTES, x[0], x[1], x[2], x[3]);
    }
}
template <int K0>
__device__ __forceinline__ void issue_qk_stage(float (&s)[32], uint32_t (&q)[48], int e, float (&o)[96], float (&inv)[2][2], const uint32_t (&q_lane)[4]) {
    constexpr int NS = 12 - K0;
    uint32_t x[NS + 1][4];
    fence_regs(q);
    wgmma_fence();
    uint64_t desc = k_desc(e);
#pragma unroll
    for (int k = 0; k < 12; k++) {
        if (k == 0) wgmma_qk_init(s, q[0], q[1], q[2], q[3], desc);
        else wgmma_qk(s, q[4 * k], q[4 * k + 1], q[4 * k + 2], q[4 * k + 3], desc);
        if (k < 11) desc += k_step(k);
        if (k == STG_CVTK) {
#pragma unroll
            for (int g = K0; g < 12; g++) cvt_out(o, g, inv, x[g - K0]);
        }
        const int j = (k - STG_K0) / STG_DK;
        if (k >= STG_K0 && (k - STG_K0) % STG_DK == 0 && j < NS) stsm_x4(q_lane[(K0 + j) & 3] + ((K0 + j) >> 2) * SLAB_BYTES, x[j][0], x[j][1], x[j][2], x[j][3]);
    }
    wgmma_commit();
}
__device__ __forceinline__ void publish_output(uint32_t oready, int lane) {
    fence_async_smem();
    __syncwarp();
    mbar_arrive_pred(oready, lane == 0);
}

__device__ __forceinline__ void stsm_x4_t(uint32_t addr, uint32_t r0, uint32_t r1, uint32_t r2, uint32_t r3) {
    asm volatile("stmatrix.sync.aligned.m8n8.x4.trans.shared.b16 [%0], {%1, %2, %3, %4};" ::"r"(addr), "r"(r0), "r"(r1), "r"(r2), "r"(r3) : "memory");
}
__device__ __forceinline__ void issue_rem_qk(float (&s)[8], int e) {
    uint64_t da = k_desc(e), db = make_desc(((SM_BASE + SM_REM) >> 4) | (1u << 16), DESC_HI);
#pragma unroll
    for (int k = 0; k < 12; k++) {
        if (k == 0) wgmma_rk_init(s, da, db);
        else wgmma_rk(s, da, db);
        if (k < 11) { da += k_step(k); db += k_step(k); }
    }
    wgmma_commit();
}
constexpr uint32_t PT_DESC_HI = (1024 >> 4) | (1u << 30);
__device__ __forceinline__ void issue_rem_pv(float (&o)[3][8], uint32_t pt, uint32_t& v) {
    const uint64_t da = make_desc(v, DESC_HI), db = make_desc(pt * (2048 >> 4) + (((SM_BASE + SM_PT) >> 4) | (1u << 16)), PT_DESC_HI);
#pragma unroll
    for (int k = 0; k < 4; k++)
#pragma unroll
        for (int m = 0; m < 3; m++) wgmma_rv(o[m], da + k * (2 * GRP_BYTES >> 4) + m * (SLAB_BYTES >> 4), db + 2 * k);
    wgmma_commit();
    next_v_desc(v);
}
__device__ __forceinline__ void rem_softmax(float (&s)[8], float (&l)[4]) {
#pragma unroll
    for (int i = 0; i < 8; i++) s[i] = ex2(s[i] * SCALE_LOG2E);
    l[0] += s[0] + s[2]; l[1] += s[1] + s[3]; l[2] += s[4] + s[6]; l[3] += s[5] + s[7];
}
__device__ __forceinline__ void rem_store(const float (&s)[8], uint32_t addr) {
    stsm_x4_t(addr, pack_bf16(s[0], s[1]), pack_bf16(s[2], s[3]), pack_bf16(s[4], s[5]), pack_bf16(s[6], s[7]));
}

__device__ __forceinline__ void mma_16816(float (&c)[4], uint32_t a0, uint32_t a1, uint32_t a2, uint32_t a3, uint32_t b0, uint32_t b1) {
    asm volatile("mma.sync.aligned.m16n8k16.row.col.f32.bf16.bf16.f32 {%0, %1, %2, %3}, {%4, %5, %6, %7}, {%8, %9}, {%0, %1, %2, %3};"
                 : "+f"(c[0]), "+f"(c[1]), "+f"(c[2]), "+f"(c[3]) : "r"(a0), "r"(a1), "r"(a2), "r"(a3), "r"(b0), "r"(b1));
}
__device__ __forceinline__ void exact_rows(const uint4* __restrict__ gq, const uint4* __restrict__ gk, const uint4* __restrict__ gv, uint4* __restrict__ go,
                                           int head, int row0, int lane) {
    constexpr int R = ROW_BYTES / 16;
    const int g = lane >> 2, c = lane & 3;
    const uint4* pq = gq + ((size_t)head * SQ + row0 + g) * R + c;
    uint4 qa[6], qb[6];
#pragma unroll
    for (int k = 0; k < 6; k++) { qa[k] = __ldg(pq + 4 * k); qb[k] = __ldg(pq + 8 * R + 4 * k); }
    float o[24][4], m[2] = {-INFINITY, -INFINITY}, l[2] = {0.f, 0.f};
#pragma unroll
    for (int i = 0; i < 24; i++) o[i][0] = o[i][1] = o[i][2] = o[i][3] = 0.f;
#pragma unroll 1
    for (int key0 = 0; key0 < SK; key0 += 16) {
        float s[2][4];
#pragma unroll
        for (int j = 0; j < 2; j++) {
            s[j][0] = s[j][1] = s[j][2] = s[j][3] = 0.f;
            const uint4* pk = gk + ((size_t)head * SK + key0 + 8 * j + g) * R + c;
#pragma unroll
            for (int k = 0; k < 6; k++) {
                const uint4 x = __ldg(pk + 4 * k);
                mma_16816(s[j], qa[k].x, qb[k].x, qa[k].y, qb[k].y, x.x, x.y);
                mma_16816(s[j], qa[k].z, qb[k].z, qa[k].w, qb[k].w, x.z, x.w);
            }
        }
#pragma unroll
        for (int h = 0; h < 2; h++) {
            float f = fmaxf(fmaxf(s[0][2 * h], s[0][2 * h + 1]), fmaxf(s[1][2 * h], s[1][2 * h + 1]));
            f = fmaxf(f, __shfl_xor_sync(0xffffffffu, f, 1));
            f = fmaxf(f, __shfl_xor_sync(0xffffffffu, f, 2));
            f = fmaxf(f, m[h]);
            const float ref = f == -INFINITY ? 0.f : f;
            const float sc = ex2((m[h] - ref) * SCALE_LOG2E);
            m[h] = f;
            l[h] *= sc;
#pragma unroll
            for (int j = 0; j < 2; j++)
#pragma unroll
                for (int e = 0; e < 2; e++) { s[j][2 * h + e] = ex2((s[j][2 * h + e] - ref) * SCALE_LOG2E); l[h] += s[j][2 * h + e]; }
#pragma unroll
            for (int i = 0; i < 24; i++) { o[i][2 * h] *= sc; o[i][2 * h + 1] *= sc; }
        }
        const uint32_t a0 = pack_bf16(s[0][0], s[0][1]), a1 = pack_bf16(s[0][2], s[0][3]), a2 = pack_bf16(s[1][0], s[1][1]), a3 = pack_bf16(s[1][2], s[1][3]);
        const uint4* pv = gv + ((size_t)head * SK + key0 + 2 * c) * R + g;
#pragma unroll
        for (int sl = 0; sl < 3; sl++) {
            const uint4 v0 = __ldg(pv + 8 * sl), v1 = __ldg(pv + R + 8 * sl), v2 = __ldg(pv + 8 * R + 8 * sl), v3 = __ldg(pv + 9 * R + 8 * sl);
            const uint32_t w0[4] = {v0.x, v0.y, v0.z, v0.w}, w1[4] = {v1.x, v1.y, v1.z, v1.w}, w2[4] = {v2.x, v2.y, v2.z, v2.w}, w3[4] = {v3.x, v3.y, v3.z, v3.w};
#pragma unroll
            for (int i = 0; i < 8; i++)
                mma_16816(o[8 * sl + i], a0, a1, a2, a3, __byte_perm(w0[i >> 1], w1[i >> 1], (i & 1) ? 0x7632 : 0x5410),
                          __byte_perm(w2[i >> 1], w3[i >> 1], (i & 1) ? 0x7632 : 0x5410));
        }
    }
#pragma unroll
    for (int h = 0; h < 2; h++) {
        l[h] += __shfl_xor_sync(0xffffffffu, l[h], 1);
        l[h] += __shfl_xor_sync(0xffffffffu, l[h], 2);
        const float inv = 1.0f / l[h];
        uint4* po = go + ((size_t)head * SQ + row0 + 8 * h + g) * R + 2 * c;
#pragma unroll
        for (int sl = 0; sl < 3; sl++)
#pragma unroll
            for (int e = 0; e < 2; e++) {
                uint32_t w[4];
#pragma unroll
                for (int i = 0; i < 4; i++) w[i] = pack_bf16(o[8 * sl + 2 * i][2 * h + e] * inv, o[8 * sl + 2 * i + 1][2 * h + e] * inv);
                po[8 * sl + e] = make_uint4(w[0], w[1], w[2], w[3]);
            }
    }
}

#define ROLE_SETUP()                                                                          \
    uint32_t bid_;                                                                            \
    asm volatile("mov.u32 %0, %%ctaid.x;" : "=r"(bid_));                                      \
    const uint32_t rank = bid_ & 1;                                                           \
    const int cluster_id = bid_ >> 1;                                                         \
    const uint16_t* sched = SCHED[cluster_id];

__device__ __forceinline__ void consumer(const uint32_t sbase, const int warp_idx, const int lane, const uint32_t zero, const uint4* __restrict__ gq,
                                         const uint4* __restrict__ gk, const uint4* __restrict__ gv, uint4* __restrict__ go) {
    ROLE_SETUP()
    const int wg = (warp_idx >> 2) - 1;
    const int tw = threadIdx.x & 127;
    const int bar_me = 1 + wg, bar_other = 2 - wg;
    const uint32_t qo = sbase + SM_QO + wg * BLK_BYTES + (warp_idx & 3) * 2 * GRP_BYTES;
    uint32_t q_lane[4];
#pragma unroll
    for (int i = 0; i < 4; i++)
        q_lane[i] = __shfl_sync(0xffffffffu, (qo + (lane & 7) * 128 + ((lane >> 3) & 1) * GRP_BYTES + (((lane >> 4) ^ (lane & 7)) << 4)) ^ (i * 32), lane);
    const uint32_t qfull = sbase + BAR_QFULL + 8 * wg, oready = sbase + BAR_OREADY + 8 * wg;

    float o[96], s[32], l[2];
    uint32_t q[48], p[16];
    uint32_t redo = 0;
    uint32_t v = V_DESC0;
    const uint32_t rel_pred = (tw == 0 || tw == 32) ? 1u : 0u;
    const uint32_t rel_base = __shfl_sync(0xffffffffu, mapa(sbase, warp_idx & 1) + BAR_DONE, 0);
    auto release = [&](int e) { mbar_arrive_cluster_pred(rel_base + 8 * (e & 3), rel_pred); };

    if (wg == 1) bar_arrive(1, 256);

    mbar_wait(qfull, 0);
    load_q_slab<0>(q, q_lane); load_q_slab<1>(q, q_lane); load_q_slab<2>(q, q_lane);
    scale_q<0, 48>(q);
    wait_blocks(sbase, 0);
    bar_sync(bar_me, 256);
    issue_qk<false>(s, q, 0);
    bar_arrive(bar_other, 256);
    const int n_items = sched[SCHED_COUNT];
    const uint32_t breaks = __shfl_sync(0xffffffffu, reinterpret_cast<const uint32_t*>(sched + SCHED_BREAKS)[wg], 0);
    wgmma_wait<0>();
    fence_regs(s);
    release(0);
    exp_range<true, 0, 32>(s, l);
    pack_p(s, p);
    wait_blocks(sbase, 1);
    wait_blocks(sbase, 2);
    float inv[2][2] = {{0.f, 0.f}, {0.f, 0.f}};
    forget(o);

#define PHASE_TAIL(B_, FIRST_, NP_, MID_, LATE_, VW_) {                                        \
    exp_range<FIRST_, 0, NP_>(s, l);                                                       \
    MID_;                                                                                  \
    fence_regs(s);                                                                         \
    if (VW_) wait_blocks(sbase, (B_) + 3);                                                 \
    else mbar_wait(sbase + BAR_DUMMY, 1);                                                  \
    wgmma_wait<0>();                                                                       \
    fence_regs(o);                                                                         \
    fence_regs(p);                                                                         \
    release((B_) + 1);                                                                     \
    if (NP_ < 32) { fence_regs(s); exp_range<false, NP_, 32>(s, l); }                      \
    pack_p(s, p);                                                                          \
    LATE_; }

    for (int t = 0;; t++) {
        const bool has_next = t + 1 < n_items, chain = !(breaks >> t & 2);
        bar_sync(bar_me, 256);
        issue_qk_stage<STAGE_SPLIT>(s, q, 1, o, inv, q_lane);
        issue_pv<true, false>(o, p, sbase, 0, v);
        bar_arrive(bar_other, 256);
        wgmma_wait<1>();
        fence_regs(s);
        PHASE_TAIL(0, false, 32, , , false)
#pragma unroll 1
        for (int b = 1; b < NBLK - 2; b++) {
            bar_sync(bar_me, 256);
            issue_qk<false>(s, q, b + 1);
            if (b == PUB_B) publish_output(oready, lane);
            issue_pv<false>(o, p, sbase, b, v);
            bar_arrive(bar_other, 256);
            wgmma_wait<1>();
            fence_regs(s);
            PHASE_TAIL(b, false, 32, , , false)
        }
        bar_sync(bar_me, 256);
        issue_qk<true>(s, q, 7);
        mbar_wait(qfull, ~t & 1);
        wgmma_wait<2>();
        load_q_slab<0>(q, q_lane);
        bb_boundary(zero, l[0], l[1]);
        issue_pv<false>(o, p, sbase, 6, v);
        bar_arrive(bar_other, 256);
        wgmma_wait<2>();
        load_q_slab<1>(q, q_lane);
        bb_boundary(zero, l[0], l[1]);
        wgmma_wait<1>();
        fence_regs(s);
        load_q_slab<2>(q, q_lane);
        bb_boundary(zero, l[0], l[1]);
        PHASE_TAIL(6, false, 32, (scale_q<0, QS_POS>(q)), (scale_q<QS_POS, 48>(q)), false)
        if (chain) {
            bar_sync(bar_me, 256);
            issue_qk<false>(s, q, 0);
            issue_pv<false>(o, p, sbase, 7, v);
            bar_arrive(bar_other, 256);
            if (NRM == 0) {
                row_normalisers(l[0], l[1], inv, redo, 1u << t, zero);
                fence_regs2(inv[0][1], inv[1][1]);
            }
            wgmma_wait<1>();
            fence_regs(s);
            if (NRM == 1) row_normalisers(after(l[0], s[30], zero), after(l[1], s[31], zero), inv, redo, 1u << t, zero);
            PHASE_TAIL(7, true, NPRE7, , (stage_output<0, STAGE_SPLIT, true>(o, inv, q_lane)), true)
            continue;
        }
        if (!has_next) {
            bar_sync(bar_me, 256);
            issue_pv<false>(o, p, sbase, 7, v);
            if ((int)breaks < 0) bar_arrive(bar_other, 256);
            row_normalisers(l[0], l[1], inv, redo, 1u << t, zero);
            wgmma_wait<0>();
            fence_regs(o);
            stage_output<0, 12, true>(o, inv, q_lane);
            break;
        }
        float rs[8], rs0[8];
        bar_sync(bar_me, 256);
        fence_regs(o); fence_regs(p);
        wgmma_fence();
        issue_rem_qk(rs0, 0);
        issue_pv<false, false, false>(o, p, sbase, 7, v);
        issue_rem_qk(rs, 1);
        bar_arrive(bar_other, 256);
        const uint32_t t_lane = sbase + (lane & 7) * 128 + ((((warp_idx & 3) * 2 + (lane >> 3 & 1)) ^ (lane & 7)) << 4);
        const uint32_t pt_lane = t_lane + SM_PT + (lane >> 4) * 1024;
        float ro[3][8], rl[4] = {0.f, 0.f, 0.f, 0.f};
        bb_boundary(zero, l[0], l[1]);
        row_normalisers(l[0], l[1], inv, redo, 1u << t, zero);
        t++;
        bb_boundary(zero, inv);
        wgmma_wait<1>();
        fence_regs(rs0); fence_regs(o);
        release(0);
        rem_softmax(rs0, rl);
        rem_store(rs0, pt_lane);
        bb_boundary(zero, rl);
        wgmma_wait<0>();
        fence_regs(rs);
        rem_softmax(rs, rl);
        rem_store(rs, pt_lane + 2048);
        fence_async_smem();
        mbar_arrive_pred(qfull, tw == 0);
#pragma unroll
        for (int i = 0; i < 8; i++) ro[0][i] = ro[1][i] = ro[2][i] = 0.f;
#pragma unroll 1
        for (int b = 0;; b++) {
            bar_sync(bar_me, 256);
            fence_regs(ro[0]); fence_regs(ro[1]); fence_regs(ro[2]);
            wgmma_fence();
            issue_rem_qk(rs, b + 2);
            issue_rem_pv(ro, b & 1, v);
            bar_arrive(bar_other, 256);
            wgmma_wait<1>();
            fence_regs(rs);
            rem_softmax(rs, rl);
            fence_regs(rs);
            bb_boundary(zero, rl[0], rl[1]);
            wgmma_wait<0>();
            fence_regs(ro[0]); fence_regs(ro[1]); fence_regs(ro[2]);
            release(b + 1);
            bar_sync(3, 128);
            rem_store(rs, pt_lane + (b & 1) * 2048);
            if (b == NBLK - 3) break;
            fence_async_smem();
            if (b == MS0) stage_output<0, 2, false>(o, inv, q_lane);
            if (b == MS0 + 1) stage_output<2, 4, false>(o, inv, q_lane);
            if (b == MS0 + 2) stage_output<4, 6, false>(o, inv, q_lane);
            if (b == MS0 + 3) stage_output<6, STAGE_SPLIT, false>(o, inv, q_lane);
        }
        {
            const uint32_t h0 = pack_bf16(rl[0], rl[1]), h1 = pack_bf16(rl[2], rl[3]);
            stsm_x4_t(pt_lane + (SM_REM - SM_PT), h0, pack_bf16(rl[0] - __uint_as_float(h0 << 16), rl[1] - __uint_as_float(h0 & 0xffff0000u)),
                      h1, pack_bf16(rl[2] - __uint_as_float(h1 << 16), rl[3] - __uint_as_float(h1 & 0xffff0000u)));
        }
        fence_async_smem();
        uint32_t ones[4] = {0x3F803F80u, 0x3F803F80u, 0x3F803F80u, 0x3F803F80u};
        auto rem_last = [&]() {
            wgmma_commit();
            issue_rem_pv(ro, 0, v);
            wait_blocks(sbase, 9);
            fence_regs(ro[0]); fence_regs(ro[1]); fence_regs(ro[2]);
            wgmma_fence();
            issue_rem_pv(ro, 1, v);
            bar_arrive(bar_other, 256);
            wgmma_wait<2>();
            fence_regs(rs);
            mbar_arrive_pred(sbase + BAR_SUMS, lane == 0);
            if (sum_unsafe(rs[0]) | sum_unsafe(rs[1]) | sum_unsafe(rs[4]) | sum_unsafe(rs[5])) redo |= 1u << t;
#pragma unroll
            for (int i = 0; i < 4; i++) asm("rcp.approx.ftz.f32 %0, %1;" : "=f"(rl[i]) : "f"(rs[(i & 2) * 2 + (i & 1)]));
        };
        auto rem_stage = [&]() {
            mbar_wait(sbase + BAR_SUMS, wg ^ 1);
            wgmma_wait<0>();
            fence_regs(ro[0]); fence_regs(ro[1]); fence_regs(ro[2]);
            release(7);
            release(0);
#pragma unroll
            for (int m = 0; m < 3; m++)
                stsm_x4_t(t_lane + SM_REM + (lane >> 4) * GRP_BYTES + m * SLAB_BYTES, pack_bf16(ro[m][0] * rl[0], ro[m][1] * rl[1]), pack_bf16(ro[m][2] * rl[0], ro[m][3] * rl[1]),
                          pack_bf16(ro[m][4] * rl[2], ro[m][5] * rl[3]), pack_bf16(ro[m][6] * rl[2], ro[m][7] * rl[3]));
        };
        const uint64_t sum_desc = make_desc(((SM_BASE + SM_REM) >> 4) | (1u << 16), PT_DESC_HI);
        fence_regs(ones);
        bar_sync(bar_me, 256);
        fence_regs(ro[0]); fence_regs(ro[1]); fence_regs(ro[2]);
        if (t + 1 == n_items) {
            wgmma_fence();
            wgmma_rl_init(rs, ones[0], ones[1], ones[2], ones[3], sum_desc);
#pragma unroll
            for (int k = 1; k < 4; k++) wgmma_rl(rs, ones[0], ones[1], ones[2], ones[3], sum_desc + 2 * k);
            rem_last();
            stage_output<STAGE_SPLIT, 12, false>(o, inv, q_lane);
            rem_stage();
            break;
        }
        fence_regs(q);
        wgmma_fence();
        {
            uint64_t desc = k_desc(0);
#pragma unroll
            for (int k = 0; k < 12; k++) {
                if (k == 0) wgmma_qk_init(s, q[0], q[1], q[2], q[3], desc);
                else wgmma_qk(s, q[4 * k], q[4 * k + 1], q[4 * k + 2], q[4 * k + 3], desc);
                if (k < 11) desc += k_step(k);
                if (k == SK0) wgmma_rl_init(rs, ones[0], ones[1], ones[2], ones[3], sum_desc);
#pragma unroll
                for (int j = 1; j < 4; j++)
                    if (k == SK0 + j * SDK) wgmma_rl(rs, ones[0], ones[1], ones[2], ones[3], sum_desc + 2 * j);
            }
        }
        rem_last();
        fence_regs(s);
        exp_range<true, 0, XN>(s, l);
        if (XN == 32) pack_p(s, p);
        else fence_regs(s);
        rem_stage();
        if (XN < 32) { fence_regs(s); exp_range<false, XN, 32>(s, l); pack_p(s, p); }
        wait_blocks(sbase, 2);
    }
    redo = __reduce_or_sync(0xffffffffu, redo);
    if (redo) asm volatile("st.shared.u32 [%0], %1;" ::"r"(sbase + SM_REDO + 4 * wg), "r"(1) : "memory");
    publish_output(oready, lane);
    if (redo) {
        mbar_wait(sbase + BAR_STORED + 8 * wg, 0);
        asm volatile("fence.proxy.async;" ::: "memory");
        for (; redo; redo &= redo - 1) {
            const Item it = decode_item(sched[__ffs(redo) - 1], rank, wg);
            const int row0 = it.grp * 8 + (warp_idx & 3) * 16;
            if (row0 < SQ) exact_rows(gq, gk, gv, go, it.head, row0, lane);
        }
    }
}

__global__ void __cluster_dims__(2, 1, 1) __launch_bounds__(384, 1)
attn_fwd_kernel(const __grid_constant__ CUtensorMap tmQ, const __grid_constant__ CUtensorMap tmK, const __grid_constant__ CUtensorMap tmV,
                const __grid_constant__ CUtensorMap tmO, const __grid_constant__ CUtensorMap tmR, const uint32_t zero,
                const uint4* __restrict__ gq, const uint4* __restrict__ gk, const uint4* __restrict__ gv, uint4* __restrict__ go) {
    extern __shared__ __align__(1024) uint8_t smem_raw[];
    const uint32_t sbase = smem_u32(smem_raw);
    const int warp_idx = __shfl_sync(0xffffffffu, threadIdx.x >> 5, 0);
    const int lane = threadIdx.x & 31;

    if (threadIdx.x == 0) {
        if ((sbase & 0x3FFFF) != SM_BASE) __trap();
        for (int i = 0; i < 4; i++) { mbar_init(sbase + BAR_FULL + 8 * i, 1); mbar_init(sbase + BAR_DONE + 8 * i, 4); }
        for (int i = 0; i < 2; i++) { mbar_init(sbase + BAR_QFULL + 8 * i, 1); mbar_init(sbase + BAR_OREADY + 8 * i, 4); mbar_init(sbase + BAR_STORED + 8 * i, 1); }
        mbar_init(sbase + BAR_DUMMY, 1);
        mbar_init(sbase + BAR_REMFREE, 1);
        mbar_init(sbase + BAR_SUMS, 4);
        asm volatile("st.shared.v2.u32 [%0], {%1, %1};" ::"r"(sbase + SM_REDO), "r"(0) : "memory");
        asm volatile("fence.mbarrier_init.release.cluster;" ::: "memory");
    } else if (threadIdx.x == 32) {
        asm volatile("prefetch.tensormap [%0];" ::"l"(&tmQ) : "memory");
        asm volatile("prefetch.tensormap [%0];" ::"l"(&tmK) : "memory");
        asm volatile("prefetch.tensormap [%0];" ::"l"(&tmV) : "memory");
        asm volatile("prefetch.tensormap [%0];" ::"l"(&tmO) : "memory");
        asm volatile("prefetch.tensormap [%0];" ::"l"(&tmR) : "memory");
    }
    __syncthreads();
    asm volatile("barrier.cluster.arrive.relaxed.aligned;" ::: "memory");
    if (warp_idx < 3 && (int)(blockIdx.x >> 1) < EARLY_CLUSTERS) {
        if (elect_one()) {
            const int w = warp_idx - 1;
            const Item q = decode_item(first_entry(blockIdx.x >> 1), blockIdx.x & 1, w);
            if (warp_idx == 0) {
                mbar_expect_tx(sbase + BAR_FULL, BLK_BYTES);
                tma_load_kv(sbase + k_addr(0), &tmK, q.head * (SK / 8), sbase + BAR_FULL);
            } else {
                mbar_expect_tx(sbase + BAR_QFULL + 8 * w, BLK_BYTES);
                tma_load_q(sbase + SM_QO + w * BLK_BYTES, &tmQ, q.grp, q.head, sbase + BAR_QFULL + 8 * w);
            }
        }
        __syncwarp();
    }
    asm volatile("barrier.cluster.wait.aligned;" ::: "memory");

    if (warp_idx < 4) {
        asm volatile("setmaxnreg.dec.sync.aligned.u32 %0;" ::"n"(PRODUCER_REGS));
        ROLE_SETUP()
        if (cluster_id >= EARLY_CLUSTERS) {
            const uint32_t t0 = clock(), d = (cluster_id - EARLY_CLUSTERS + 1) * START_STEP;
            while ((uint32_t)clock() - t0 < d) __nanosleep(20);
        }
        if (warp_idx == 0) {
            if (elect_one()) {
                auto load = [&](const CUtensorMap* tm, uint32_t owner, const Item& it, int blk, uint32_t dst, uint32_t full) {
                    const int grp = it.head * (SK / 8) + blk * 8;
                    if (!it.mc) tma_load_kv(sbase + dst, tm, grp, full);
                    else if (rank == owner) tma_load_kv_mc(sbase + dst, tm, grp, full);
                };
                Item iv = decode_item(first_entry(cluster_id), rank, 0), ik = iv;
                for (int e = cluster_id < EARLY_CLUSTERS; e < 2; e++) {
                    mbar_expect_tx(sbase + BAR_FULL + 8 * e, BLK_BYTES);
                    load(&tmK, 0, ik, e, k_addr(e), sbase + BAR_FULL + 8 * e);
                }
                uint32_t v = SM_V;
                bool more = true;
                for (int t = 1; more; t++) {
#pragma unroll 1
                    for (int e = 2; e < NBLK + 2; e++) {
                        if (e == NBLK) { more = t < sched[SCHED_COUNT]; ik = decode_item(sched[t], rank, 0); }
                        const uint32_t full = sbase + BAR_FULL + 8 * (e & 3);
                        mbar_wait(full + (BAR_DONE - BAR_FULL), ~e >> 2 & 1);
                        mbar_expect_tx(full, more ? 2 * BLK_BYTES : BLK_BYTES);
                        load(&tmV, 1, iv, e - 2, v, full);
                        if (more) load(&tmK, 0, ik, e & 7, k_addr(e), full);
                        next_v(v);
                    }
                    iv = ik;
                }
            }
        } else if (warp_idx < 3) {
            if (elect_one()) {
                const int w = warp_idx - 1;
                const uint32_t buf = sbase + SM_QO + w * BLK_BYTES;
                const uint32_t qfull = sbase + BAR_QFULL + 8 * w, oready = sbase + BAR_OREADY + 8 * w;
                if (cluster_id >= EARLY_CLUSTERS) {
                    const Item q = decode_item(first_entry(cluster_id), rank, w);
                    mbar_expect_tx(qfull, BLK_BYTES);
                    tma_load_q(buf, &tmQ, q.grp, q.head, qfull);
                }
                const int n_items = sched[SCHED_COUNT];
                for (int r = 0, phase = 0; r <= n_items; r++, phase ^= 1) {
                    const Item rq = decode_item(sched[r + 1], rank, w), q = decode_item(sched[r + 1 + rq.rem], rank, w);
                    const Item ro = decode_item(sched[r > 0 ? r - 1 : 0], rank, w), o = decode_item(sched[r > 0 ? r - 1 - ro.rem : 0], rank, w);
                    mbar_wait(oready, phase);
                    if (r > 0) {
                        tma_store_o(&tmO, buf, o.grp, o.head);
                        if (ro.rem) tma_store_o(&tmO, sbase + SM_REM, ro.grp, ro.head);
                        bulk_commit();
                        bulk_wait_read();
                        if (ro.rem) mbar_arrive(sbase + BAR_REMFREE);
                    }
                    if (r < n_items) {
                        const bool full = r + 1 + rq.rem < n_items;
                        mbar_expect_tx(qfull, (rq.rem ? REM_BYTES : 0) + (full ? BLK_BYTES : 0));
                        if (full) tma_load_q(buf, &tmQ, q.grp, q.head, qfull);
                        if (rq.rem) {
                            mbar_wait(sbase + BAR_REMFREE, w);
                            tma_load_q(sbase + SM_REM, &tmR, rq.grp, rq.head, qfull);
                        }
                        r += rq.rem;
                    }
                }
                uint32_t redo;
                asm volatile("ld.shared.u32 %0, [%1];" : "=r"(redo) : "r"(sbase + SM_REDO + 4 * w) : "memory");
                if (redo) {
                    asm volatile("cp.async.bulk.wait_group 0;\nfence.proxy.async;" ::: "memory");
                    mbar_arrive(sbase + BAR_STORED + 8 * w);
                }
            }
        }
        else if (T_KVPF && elect_one()) {
            const int n_items = sched[SCHED_COUNT];
            const char* kv = reinterpret_cast<const char*>(rank ? gv : gk);
#pragma unroll 1
            for (int e = 4; e < NBLK * n_items; e++) {
                mbar_wait(sbase + BAR_DONE + 8 * (e & 3), ~e >> 2 & 1);
                const int x = e + T_KVPF - 2 * rank;
                const uint32_t it = sched[x >> 3];
                if (x >> 3 < n_items && (it & 3) != 3)
                    asm volatile("cp.async.bulk.prefetch.L2.global [%0], %1;" ::"l"(kv + ((it >> 2) * 24 + (x & 7) * 3 + (it & 3)) * (BLK_BYTES / 3)), "r"(BLK_BYTES / 3) : "memory");
            }
        }
    } else {
        asm volatile("setmaxnreg.inc.sync.aligned.u32 %0;" ::"n"(CONSUMER_REGS));
        consumer(sbase, warp_idx, lane, zero, gq, gk, gv, go);
    }
    asm volatile("barrier.cluster.arrive.relaxed.aligned;\nbarrier.cluster.wait.aligned;" ::: "memory");
}

typedef CUresult (*EncodeTiledFn)(CUtensorMap*, CUtensorMapDataType, cuuint32_t, void*, const cuuint64_t*, const cuuint64_t*,
                                  const cuuint32_t*, const cuuint32_t*, CUtensorMapInterleave, CUtensorMapSwizzle,
                                  CUtensorMapL2promotion, CUtensorMapFloatOOBfill);

}

extern "C" void kernel_launch(void* const* d_in, const int* in_sizes, int n_in, void* d_out, int out_size) {
    (void)in_sizes; (void)n_in; (void)out_size;
    static CUtensorMap tmQ, tmK, tmV, tmO, tmR;
    static void* cached[4] = {nullptr, nullptr, nullptr, nullptr};
    if (cached[0] != d_in[0] || cached[1] != d_in[1] || cached[2] != d_in[2] || cached[3] != d_out) {
        void* fn = nullptr;
        cudaDriverEntryPointQueryResult qr;
        cudaGetDriverEntryPoint("cuTensorMapEncodeTiled", &fn, cudaEnableDefault, &qr);
        EncodeTiledFn enc = (EncodeTiledFn)fn;
        const cuuint32_t es[5] = {1, 1, 1, 1, 1};
        const cuuint32_t box[5] = {64, 8, 3, 8, 1};
        const cuuint32_t box_rem[5] = {64, 8, 3, 2, 1};
        {
            cuuint64_t gd[5] = {64, 8, 3, SQ / 8, NHEADS};
            cuuint64_t gs[4] = {ROW_BYTES, 128, 8 * ROW_BYTES, (cuuint64_t)SQ * ROW_BYTES};
            enc(&tmQ, CU_TENSOR_MAP_DATA_TYPE_BFLOAT16, 5, d_in[0], gd, gs, box, es, CU_TENSOR_MAP_INTERLEAVE_NONE,
                CU_TENSOR_MAP_SWIZZLE_128B, CU_TENSOR_MAP_L2_PROMOTION_NONE, CU_TENSOR_MAP_FLOAT_OOB_FILL_NONE);
            enc(&tmR, CU_TENSOR_MAP_DATA_TYPE_BFLOAT16, 5, d_in[0], gd, gs, box_rem, es, CU_TENSOR_MAP_INTERLEAVE_NONE,
                CU_TENSOR_MAP_SWIZZLE_128B, CU_TENSOR_MAP_L2_PROMOTION_NONE, CU_TENSOR_MAP_FLOAT_OOB_FILL_NONE);
            enc(&tmO, CU_TENSOR_MAP_DATA_TYPE_BFLOAT16, 5, d_out, gd, gs, box, es, CU_TENSOR_MAP_INTERLEAVE_NONE,
                CU_TENSOR_MAP_SWIZZLE_128B, CU_TENSOR_MAP_L2_PROMOTION_NONE, CU_TENSOR_MAP_FLOAT_OOB_FILL_NONE);
        }
        {
            cuuint64_t gd[4] = {64, 8, 3, (cuuint64_t)NHEADS * SK / 8};
            cuuint64_t gs[3] = {ROW_BYTES, 128, 8 * ROW_BYTES};
            enc(&tmK, CU_TENSOR_MAP_DATA_TYPE_BFLOAT16, 4, d_in[1], gd, gs, box, es, CU_TENSOR_MAP_INTERLEAVE_NONE,
                CU_TENSOR_MAP_SWIZZLE_128B, CU_TENSOR_MAP_L2_PROMOTION_NONE, CU_TENSOR_MAP_FLOAT_OOB_FILL_NONE);
            enc(&tmV, CU_TENSOR_MAP_DATA_TYPE_BFLOAT16, 4, d_in[2], gd, gs, box, es, CU_TENSOR_MAP_INTERLEAVE_NONE,
                CU_TENSOR_MAP_SWIZZLE_128B, CU_TENSOR_MAP_L2_PROMOTION_NONE, CU_TENSOR_MAP_FLOAT_OOB_FILL_NONE);
        }
        cudaFuncSetAttribute(attn_fwd_kernel, cudaFuncAttributeMaxDynamicSharedMemorySize, SMEM_BYTES);
        cached[0] = d_in[0]; cached[1] = d_in[1]; cached[2] = d_in[2]; cached[3] = d_out;
    }
    attn_fwd_kernel<<<2 * NUM_CLUSTERS, 384, SMEM_BYTES, cudaStreamPerThread>>>(tmQ, tmK, tmV, tmO, tmR, 0u, (const uint4*)d_in[0], (const uint4*)d_in[1],
                                                                                (const uint4*)d_in[2], (uint4*)d_out);
}
```

```cpp
#include <cuda_runtime.h>
#include <cuda_bf16.h>
#include <cuda.h>
#include <stdint.h>

namespace {

constexpr int NHEADS = 512;
constexpr int SQ = 848;
constexpr int SK = 512;
constexpr int DH = 192;
constexpr int ROW_BYTES = DH * 2;
constexpr int NBLK = SK / 64;
constexpr int NUM_CLUSTERS = 66;

constexpr uint32_t GRP_BYTES = 3072, SLAB_BYTES = 1024;
constexpr uint32_t BLK_BYTES = 64 * ROW_BYTES;
constexpr uint32_t REM_BYTES = 16 * ROW_BYTES;
constexpr uint32_t SM_BASE = 1024;
constexpr uint32_t SM_BAR = 0;
constexpr uint32_t SM_REM = 1024;
constexpr uint32_t SM_V = SM_REM + REM_BYTES;
constexpr uint32_t SM_K = SM_V + 3 * BLK_BYTES;
constexpr uint32_t SM_QO = SM_K + 4 * BLK_BYTES;
constexpr uint32_t SM_PT = SM_QO + 2 * BLK_BYTES;
constexpr uint32_t SMEM_BYTES = SM_PT + 2 * 2048;
#define T_KVPF 4
#define KROT 2
constexpr uint32_t BAR_FULL = SM_BAR;
constexpr uint32_t BAR_DONE = BAR_FULL + 32;
constexpr uint32_t BAR_QFULL = BAR_DONE + 32;
constexpr uint32_t BAR_OREADY = BAR_QFULL + 16;
constexpr uint32_t BAR_STORED = BAR_OREADY + 16;
constexpr uint32_t BAR_DUMMY = BAR_STORED + 16;
constexpr uint32_t BAR_REMFREE = BAR_DUMMY + 8;
constexpr uint32_t BAR_SUMS = BAR_REMFREE + 8;
constexpr uint32_t SM_REDO = BAR_SUMS + 8;
static_assert(SMEM_BYTES <= 232448, "smem");

constexpr int PRODUCER_REGS = 24, CONSUMER_REGS = 240;
#define STAGE_SPLIT 4
#define STG_CVTK 7
#define STG_POS 0xBA987654
#define STG_N1 4
#define P6N 24
#define MS0 1
#define SK0 0
#define SDK 2
#define PUB_B 1
constexpr float SCALE_LOG2E = 0.07216878364870323f * 1.4426950408889634f;
constexpr uint32_t SCALE_HI = 0x3DD53DD5u, SCALE_LO = 0x38EE38EEu;
constexpr uint32_t SUM_LOW = (127u - 14u) << 23, SUM_HIGH = (127u + 32u) << 23;

constexpr int EARLY_CLUSTERS = 10, START_STEP = 70;
constexpr int SCHED_COUNT = 29, SCHED_BREAKS = 30;
__constant__ __align__(8) uint16_t SCHED[NUM_CLUSTERS][36] = {
    {0, 3, 150, 223, 302, 378, 454, 530, 605, 659, 756, 832, 910, 967, 1056, 1136, 1195, 1281, 1360, 1423, 1505, 1580, 1660, 1737, 1787, 1876, 1903, 1984, 0, 28, 8200, 37896, 514, 4353, 0, 0},
    {1, 11, 152, 228, 304, 381, 460, 519, 606, 667, 757, 823, 908, 982, 1057, 1107, 1206, 1282, 1343, 1425, 1467, 1552, 1633, 1687, 1756, 1830, 1908, 1985, 0, 28, 2176, 36996, 33282, 4112, 0, 0},
    {2, 19, 153, 229, 305, 382, 461, 538, 607, 684, 747, 833, 887, 984, 1058, 1137, 1213, 1288, 1365, 1441, 1499, 1590, 1669, 1743, 1817, 1875, 1960, 1975, 0, 28, 4352, 39040, 1026, 4624, 0, 0},
    {4, 88, 165, 227, 306, 384, 447, 532, 608, 675, 758, 834, 895, 985, 1060, 1115, 1208, 1284, 1361, 1437, 1487, 1581, 1635, 1713, 1796, 1877, 1961, 1983, 0, 28, 4160, 38928, 33288, 4160, 0, 0},
    {5, 27, 154, 230, 303, 380, 456, 533, 595, 682, 760, 836, 912, 989, 1063, 1138, 1214, 1283, 1362, 1438, 1517, 1592, 1655, 1738, 1818, 1883, 1962, 1991, 0, 28, 16400, 38976, 258, 4610, 0, 0},
    {6, 89, 166, 241, 320, 387, 462, 527, 609, 685, 761, 827, 913, 975, 1061, 1140, 1216, 1289, 1366, 1442, 1507, 1593, 1663, 1740, 1795, 1878, 1911, 1986, 0, 28, 8320, 37952, 2080, 4368, 0, 0},
    {8, 35, 156, 232, 308, 385, 464, 540, 617, 687, 762, 838, 907, 990, 1064, 1141, 1207, 1290, 1355, 1440, 1495, 1582, 1661, 1741, 1803, 1880, 1919, 1988, 0, 28, 512, 37905, 4098, 4356, 0, 0},
    {9, 90, 168, 242, 321, 397, 459, 541, 615, 686, 764, 840, 914, 979, 1065, 1135, 1217, 1292, 1368, 1435, 1518, 1591, 1662, 1715, 1797, 1839, 1909, 1989, 0, 28, 33024, 37408, 8256, 4232, 0, 0},
    {10, 92, 169, 244, 322, 398, 477, 556, 634, 691, 770, 839, 916, 992, 1066, 1142, 1211, 1293, 1367, 1444, 1515, 1594, 1671, 1742, 1820, 1891, 1964, 1999, 0, 28, 2048, 38980, 512, 4625, 0, 0},
    {12, 93, 170, 245, 307, 386, 455, 534, 610, 688, 755, 837, 903, 986, 1062, 1123, 1209, 1285, 1364, 1431, 1506, 1563, 1634, 1714, 1751, 1832, 1910, 1990, 0, 28, 4160, 37128, 33808, 4128, 0, 0},
    {13, 94, 173, 249, 326, 405, 484, 564, 644, 721, 787, 854, 934, 1012, 1088, 1166, 1242, 1320, 1400, 1480, 1558, 1641, 1695, 1765, 1844, 1924, 2008, 0, 0, 27, 0, 34880, 1024, 2048, 0, 0},
    {14, 96, 176, 252, 328, 406, 485, 565, 645, 722, 801, 878, 956, 1037, 1116, 1196, 1274, 1331, 1401, 1481, 1535, 1610, 1688, 1768, 1846, 1926, 2010, 0, 0, 27, 0, 34832, 0, 2050, 0, 0},
    {16, 97, 177, 253, 329, 408, 486, 566, 627, 698, 777, 857, 937, 1014, 1090, 1168, 1244, 1321, 1402, 1482, 1561, 1615, 1690, 1770, 1849, 1929, 2014, 0, 0, 27, 0, 34848, 256, 2048, 0, 0},
    {17, 98, 178, 254, 330, 410, 490, 570, 635, 700, 780, 860, 940, 1018, 1093, 1170, 1246, 1322, 1404, 1484, 1562, 1644, 1724, 1775, 1853, 1933, 2018, 0, 0, 27, 0, 34944, 256, 2048, 0, 0},
    {18, 100, 180, 257, 333, 413, 494, 573, 650, 728, 806, 884, 958, 1040, 1118, 1155, 1250, 1326, 1408, 1488, 1565, 1623, 1696, 1777, 1857, 1937, 2022, 0, 0, 27, 0, 34848, 32768, 2048, 0, 0},
    {20, 43, 157, 233, 310, 389, 466, 544, 622, 702, 784, 864, 927, 996, 1072, 1150, 1228, 1305, 1385, 1462, 1538, 1618, 1698, 1781, 1861, 1941, 2026, 0, 0, 27, 4096, 34816, 2, 2048, 0, 0},
    {21, 51, 158, 234, 312, 390, 468, 545, 624, 704, 785, 865, 942, 1022, 1097, 1176, 1253, 1329, 1410, 1490, 1568, 1631, 1701, 1784, 1865, 1945, 2030, 0, 0, 27, 0, 34848, 2, 2048, 0, 0},
    {22, 59, 160, 236, 313, 392, 469, 546, 625, 705, 786, 868, 945, 1025, 1100, 1178, 1256, 1332, 1413, 1492, 1569, 1649, 1726, 1806, 1889, 1959, 2034, 0, 0, 27, 0, 35328, 2, 2048, 0, 0},
    {24, 67, 161, 237, 314, 393, 472, 543, 614, 692, 768, 844, 920, 998, 1074, 1153, 1230, 1309, 1389, 1466, 1544, 1625, 1706, 1789, 1870, 1952, 2038, 0, 0, 27, 128, 34816, 2, 2048, 0, 0},
    {25, 101, 182, 261, 340, 403, 473, 548, 626, 706, 788, 869, 946, 1026, 1101, 1181, 1260, 1336, 1417, 1497, 1559, 1626, 1708, 1790, 1872, 1953, 2041, 0, 0, 27, 0, 34832, 32, 2048, 0, 0},
    {26, 102, 184, 262, 342, 421, 504, 584, 662, 738, 816, 893, 966, 1048, 1126, 1202, 1259, 1338, 1420, 1500, 1574, 1654, 1732, 1812, 1893, 1969, 2031, 0, 0, 27, 0, 35840, 0, 2049, 0, 0},
    {28, 104, 185, 264, 344, 422, 467, 549, 628, 708, 767, 845, 921, 1000, 1076, 1154, 1232, 1312, 1392, 1469, 1546, 1629, 1710, 1793, 1874, 1957, 2045, 0, 0, 27, 1024, 34816, 64, 2048, 0, 0},
    {29, 105, 186, 265, 345, 424, 475, 550, 629, 709, 789, 870, 948, 1029, 1104, 1184, 1262, 1341, 1422, 1504, 1578, 1658, 1736, 1816, 1871, 1958, 2046, 0, 0, 27, 0, 35072, 64, 2048, 0, 0},
    {30, 106, 188, 243, 316, 394, 474, 552, 630, 710, 792, 873, 950, 1032, 1105, 1185, 1264, 1342, 1424, 1463, 1548, 1595, 1672, 1748, 1822, 1898, 1974, 0, 0, 27, 0, 2056, 8, 34848, 0, 0},
    {32, 75, 162, 238, 317, 396, 476, 554, 633, 713, 775, 846, 924, 1002, 1078, 1158, 1219, 1294, 1369, 1446, 1522, 1598, 1674, 1750, 1825, 1901, 1977, 0, 0, 27, 1024, 2048, 2, 34817, 0, 0},
    {33, 83, 164, 240, 318, 383, 458, 537, 616, 693, 769, 848, 925, 1004, 1080, 1160, 1236, 1316, 1394, 1472, 1550, 1632, 1712, 1794, 1827, 1904, 1980, 0, 0, 27, 32, 2048, 2, 35072, 0, 0},
    {34, 108, 189, 266, 348, 428, 506, 563, 636, 714, 794, 855, 926, 987, 1068, 1144, 1218, 1296, 1370, 1448, 1524, 1601, 1677, 1754, 1829, 1906, 1982, 0, 0, 27, 2048, 2048, 8320, 34816, 0, 0},
    {36, 109, 190, 268, 349, 429, 491, 557, 637, 716, 783, 849, 928, 1005, 1081, 1161, 1237, 1291, 1372, 1449, 1525, 1602, 1678, 1757, 1833, 1912, 1993, 0, 0, 27, 1024, 2048, 64, 34818, 0, 0},
    {37, 110, 192, 270, 352, 432, 509, 588, 668, 742, 820, 900, 974, 1053, 1132, 1210, 1286, 1347, 1429, 1510, 1575, 1636, 1716, 1800, 1843, 1913, 1996, 0, 0, 27, 0, 2064, 0, 35074, 0, 0},
    {38, 112, 155, 246, 324, 401, 480, 551, 618, 694, 772, 850, 930, 1008, 1084, 1162, 1238, 1299, 1374, 1452, 1528, 1605, 1681, 1760, 1836, 1916, 1998, 0, 0, 27, 128, 2048, 4, 34818, 0, 0},
    {40, 113, 163, 248, 325, 402, 481, 560, 641, 720, 800, 877, 954, 1036, 1112, 1192, 1269, 1327, 1397, 1476, 1554, 1603, 1682, 1761, 1837, 1917, 2001, 0, 0, 27, 0, 2050, 4, 34848, 0, 0},
    {41, 91, 172, 239, 309, 371, 457, 536, 612, 689, 765, 841, 917, 993, 1069, 1145, 1221, 1298, 1376, 1453, 1529, 1606, 1684, 1762, 1838, 1918, 2002, 0, 0, 27, 8, 2048, 34, 34816, 0, 0},
    {42, 114, 193, 274, 331, 404, 482, 561, 642, 703, 773, 852, 932, 1009, 1085, 1164, 1240, 1318, 1398, 1478, 1557, 1640, 1720, 1763, 1841, 1921, 2005, 0, 0, 27, 512, 2048, 16, 34944, 0, 0},
    {44, 99, 174, 250, 319, 388, 465, 542, 620, 697, 776, 856, 936, 1013, 1067, 1146, 1222, 1300, 1378, 1456, 1532, 1609, 1686, 1766, 1845, 1925, 2009, 0, 0, 27, 16, 2048, 16386, 34816, 0, 0},
    {45, 116, 196, 277, 356, 436, 513, 590, 643, 724, 802, 880, 957, 999, 1089, 1147, 1224, 1301, 1380, 1457, 1533, 1612, 1689, 1769, 1848, 1928, 2012, 0, 0, 27, 8192, 2048, 33024, 34816, 0, 0},
    {46, 117, 197, 278, 339, 409, 488, 568, 646, 725, 804, 881, 935, 1016, 1092, 1169, 1245, 1315, 1381, 1458, 1534, 1613, 1692, 1772, 1850, 1930, 2016, 0, 0, 27, 4096, 2048, 16, 34818, 0, 0},
    {48, 118, 171, 256, 332, 412, 492, 572, 649, 726, 805, 882, 943, 1020, 1094, 1172, 1248, 1324, 1405, 1485, 1539, 1616, 1694, 1774, 1854, 1934, 2020, 0, 0, 27, 4096, 2048, 4, 34832, 0, 0},
    {49, 120, 201, 251, 334, 414, 496, 574, 652, 729, 808, 885, 960, 1041, 1120, 1167, 1252, 1328, 1409, 1489, 1566, 1646, 1707, 1778, 1858, 1938, 2024, 0, 0, 27, 32768, 2048, 8, 34880, 0, 0},
    {50, 121, 202, 282, 361, 440, 517, 593, 672, 746, 824, 904, 978, 1035, 1121, 1198, 1277, 1354, 1434, 1514, 1583, 1648, 1725, 1779, 1862, 1942, 2028, 0, 0, 27, 0, 2064, 8192, 34944, 0, 0},
    {52, 122, 179, 258, 336, 417, 498, 577, 656, 732, 799, 866, 944, 1024, 1098, 1177, 1254, 1330, 1412, 1451, 1541, 1621, 1702, 1785, 1866, 1946, 2032, 0, 0, 27, 1024, 2048, 4, 34824, 0, 0},
    {53, 124, 205, 259, 337, 399, 470, 531, 613, 690, 766, 842, 918, 997, 1073, 1152, 1229, 1308, 1388, 1465, 1542, 1622, 1704, 1786, 1868, 1949, 2036, 0, 0, 27, 32, 2048, 136, 34816, 0, 0},
    {54, 107, 181, 260, 338, 418, 500, 578, 657, 733, 810, 888, 962, 1044, 1124, 1175, 1257, 1333, 1414, 1494, 1570, 1650, 1728, 1808, 1890, 1963, 2040, 0, 0, 27, 32768, 2048, 2, 35328, 0, 0},
    {56, 125, 208, 267, 341, 420, 502, 581, 660, 736, 813, 890, 951, 1028, 1102, 1182, 1235, 1310, 1390, 1468, 1545, 1628, 1709, 1792, 1873, 1954, 2042, 0, 0, 27, 4096, 2048, 8, 34817, 0, 0},
    {57, 126, 209, 288, 366, 444, 520, 596, 674, 749, 803, 894, 968, 1049, 1128, 1183, 1261, 1340, 1421, 1501, 1576, 1656, 1733, 1813, 1894, 1970, 2035, 0, 0, 27, 32768, 2048, 1024, 35840, 0, 0},
    {58, 128, 210, 289, 368, 445, 521, 597, 651, 740, 817, 896, 969, 1050, 1129, 1204, 1280, 1358, 1415, 1502, 1577, 1657, 1734, 1814, 1896, 1972, 2043, 0, 0, 27, 0, 2052, 256, 35840, 0, 0},
    {60, 129, 212, 275, 346, 425, 505, 585, 664, 727, 790, 872, 949, 1030, 1083, 1156, 1233, 1313, 1393, 1447, 1520, 1596, 1670, 1746, 1821, 1897, 1973, 0, 0, 27, 512, 34824, 16392, 2048, 0, 0},
    {61, 130, 213, 290, 355, 426, 487, 553, 632, 712, 793, 843, 922, 1001, 1077, 1157, 1234, 1314, 1375, 1445, 1521, 1597, 1673, 1749, 1824, 1900, 1976, 0, 0, 27, 64, 34820, 2064, 2048, 0, 0},
    {62, 132, 214, 292, 369, 446, 522, 598, 676, 750, 811, 897, 970, 1052, 1130, 1205, 1271, 1344, 1379, 1470, 1549, 1630, 1679, 1752, 1826, 1902, 1978, 0, 0, 27, 0, 34881, 1024, 2052, 0, 0},
    {64, 133, 216, 293, 370, 448, 524, 587, 665, 741, 818, 898, 972, 1007, 1106, 1186, 1265, 1345, 1387, 1473, 1527, 1600, 1676, 1753, 1828, 1905, 1981, 0, 0, 27, 8192, 34832, 128, 2052, 0, 0},
    {65, 134, 217, 294, 372, 449, 525, 600, 677, 752, 828, 867, 973, 1015, 1108, 1188, 1266, 1346, 1426, 1508, 1584, 1664, 1744, 1811, 1881, 1927, 1992, 0, 0, 27, 8192, 35328, 2048, 2176, 0, 0},
    {66, 136, 187, 269, 350, 430, 508, 586, 666, 735, 796, 874, 952, 1033, 1109, 1189, 1268, 1348, 1428, 1509, 1585, 1665, 1723, 1798, 1882, 1935, 1994, 0, 0, 27, 512, 35328, 4, 2112, 0, 0},
    {68, 137, 195, 272, 327, 400, 478, 558, 638, 717, 797, 859, 929, 1006, 1082, 1143, 1220, 1297, 1373, 1450, 1526, 1604, 1680, 1758, 1834, 1914, 1997, 0, 0, 27, 32784, 34816, 2052, 2048, 0, 0},
    {69, 138, 218, 296, 373, 435, 510, 575, 640, 718, 798, 876, 953, 1034, 1110, 1190, 1243, 1317, 1396, 1474, 1553, 1637, 1717, 1801, 1884, 1943, 2000, 0, 0, 27, 128, 35328, 32, 2049, 0, 0},
    {70, 140, 220, 297, 374, 450, 526, 601, 678, 753, 829, 875, 976, 1023, 1113, 1193, 1270, 1349, 1430, 1512, 1586, 1666, 1745, 1819, 1885, 1965, 2007, 0, 0, 27, 8192, 35840, 2048, 2176, 0, 0},
    {72, 141, 203, 273, 353, 433, 512, 589, 669, 744, 821, 901, 977, 1031, 1114, 1194, 1272, 1350, 1395, 1477, 1556, 1638, 1718, 1759, 1840, 1920, 2004, 0, 0, 27, 8192, 34944, 4, 2052, 0, 0},
    {73, 115, 194, 276, 354, 434, 503, 562, 619, 696, 774, 853, 933, 1010, 1086, 1165, 1241, 1311, 1377, 1454, 1530, 1608, 1685, 1764, 1842, 1922, 2006, 0, 0, 27, 64, 34818, 258, 2048, 0, 0},
    {74, 142, 221, 298, 376, 452, 528, 602, 680, 754, 830, 909, 988, 1051, 1133, 1191, 1273, 1352, 1432, 1513, 1588, 1643, 1721, 1802, 1886, 1966, 2015, 0, 0, 27, 32768, 35840, 8192, 2080, 0, 0},
    {76, 144, 222, 283, 357, 437, 514, 592, 670, 745, 822, 902, 959, 1038, 1117, 1197, 1276, 1353, 1433, 1475, 1560, 1642, 1722, 1804, 1888, 1951, 2013, 0, 0, 27, 4096, 35328, 8, 2056, 0, 0},
    {77, 123, 198, 280, 358, 415, 489, 569, 648, 707, 778, 858, 938, 1017, 1079, 1148, 1225, 1302, 1382, 1460, 1536, 1614, 1693, 1773, 1852, 1932, 2017, 0, 0, 27, 16416, 34816, 514, 2048, 0, 0},
    {78, 131, 200, 281, 360, 423, 493, 555, 621, 701, 781, 861, 941, 1021, 1096, 1173, 1249, 1325, 1406, 1486, 1564, 1645, 1703, 1776, 1856, 1936, 2021, 0, 0, 27, 32, 34880, 130, 2048, 0, 0},
    {80, 145, 224, 300, 363, 438, 516, 583, 653, 715, 782, 862, 919, 994, 1070, 1149, 1226, 1304, 1384, 1461, 1537, 1617, 1697, 1780, 1860, 1940, 2025, 0, 0, 27, 4224, 34816, 528, 2048, 0, 0},
    {81, 146, 211, 284, 351, 416, 497, 576, 654, 730, 809, 886, 961, 1042, 1091, 1174, 1231, 1306, 1386, 1464, 1540, 1620, 1700, 1782, 1864, 1944, 2029, 0, 0, 27, 16, 34817, 16388, 2048, 0, 0},
    {82, 139, 204, 285, 362, 441, 518, 594, 673, 748, 825, 905, 980, 1047, 1122, 1200, 1278, 1356, 1436, 1516, 1589, 1668, 1731, 1805, 1855, 1948, 2033, 0, 0, 27, 8192, 35072, 2, 2112, 0, 0},
    {84, 148, 225, 301, 377, 453, 529, 604, 681, 739, 826, 906, 981, 1054, 1134, 1212, 1279, 1357, 1403, 1493, 1551, 1624, 1705, 1788, 1869, 1950, 2037, 0, 0, 27, 0, 34833, 512, 2052, 0, 0},
    {85, 147, 206, 286, 364, 431, 501, 580, 658, 734, 812, 889, 964, 1045, 1099, 1180, 1258, 1334, 1416, 1496, 1572, 1652, 1729, 1809, 1892, 1968, 2023, 0, 0, 27, 32, 35840, 16386, 2048, 0, 0},
    {86, 149, 226, 291, 365, 442, 511, 582, 661, 737, 814, 892, 965, 1046, 1125, 1201, 1251, 1337, 1418, 1498, 1573, 1653, 1730, 1810, 1863, 1956, 2044, 0, 0, 27, 64, 35072, 8, 2049, 0, 0},
};

__device__ __forceinline__ uint32_t smem_u32(const void* p) { return (uint32_t)__cvta_generic_to_shared(p); }
__device__ __forceinline__ void mbar_init(uint32_t bar, uint32_t cnt) {
    asm volatile("mbarrier.init.shared::cta.b64 [%0], %1;" ::"r"(bar), "r"(cnt));
}
__device__ __forceinline__ void mbar_expect_tx(uint32_t bar, uint32_t bytes) {
    asm volatile("mbarrier.arrive.expect_tx.shared::cta.b64 _, [%0], %1;" ::"r"(bar), "r"(bytes) : "memory");
}
__device__ __forceinline__ void mbar_arrive(uint32_t bar) {
    asm volatile("mbarrier.arrive.shared::cta.b64 _, [%0];" ::"r"(bar) : "memory");
}
__device__ __forceinline__ void mbar_arrive_cluster_pred(uint32_t addr, uint32_t pred) {
    asm volatile(
        "{\n.reg .pred p;\n"
        "setp.ne.u32 p, %1, 0;\n"
        "@p mbarrier.arrive.shared::cluster.b64 _, [%0];\n}\n" ::"r"(addr), "r"(pred) : "memory");
}
__device__ __forceinline__ void mbar_arrive_pred(uint32_t addr, uint32_t pred) {
    asm volatile(
        "{\n.reg .pred p;\n"
        "setp.ne.u32 p, %1, 0;\n"
        "@p mbarrier.arrive.shared::cta.b64 _, [%0];\n}\n" ::"r"(addr), "r"(pred) : "memory");
}
__device__ __forceinline__ uint32_t mapa(uint32_t addr, uint32_t cta) {
    uint32_t r;
    asm("mapa.shared::cluster.u32 %0, %1, %2;" : "=r"(r) : "r"(addr), "r"(cta));
    return r;
}
__device__ __forceinline__ void mbar_wait(uint32_t bar, uint32_t parity) {
    asm volatile(
        "{\n.reg .pred p;\n"
        "WAIT_LOOP:\n"
        "mbarrier.try_wait.parity.shared::cta.b64 p, [%0], %1;\n"
        "@p bra WAIT_DONE;\n"
        "bra WAIT_LOOP;\n"
        "WAIT_DONE:\n}\n" ::"r"(bar), "r"(parity) : "memory");
}
__device__ __forceinline__ void mbar_sleep(uint32_t bar, uint32_t parity) {
    asm volatile(
        "{\n.reg .pred p;\n"
        "WAIT_LOOP:\n"
        "mbarrier.try_wait.parity.shared::cta.b64 p, [%0], %1, 0x989680;\n"
        "@p bra WAIT_DONE;\n"
        "bra WAIT_LOOP;\n"
        "WAIT_DONE:\n}\n" ::"r"(bar), "r"(parity) : "memory");
}
__device__ __forceinline__ bool elect_one() {
    uint32_t pred;
    asm volatile("{\n.reg .pred p;\nelect.sync _|p, 0xffffffff;\nselp.u32 %0, 1, 0, p;\n}\n" : "=r"(pred));
    return pred != 0;
}
__device__ __forceinline__ void tma_load_kv(uint32_t dst, const CUtensorMap* tm, int g, uint32_t bar) {
    asm volatile(
        "cp.async.bulk.tensor.4d.shared::cluster.global.mbarrier::complete_tx::bytes [%0], [%1, {%3, %3, %3, %4}], [%2];" ::"r"(dst),
        "l"(tm), "r"(bar), "r"(0), "r"(g)
        : "memory");
}
__device__ __forceinline__ void tma_load_kv_mc(uint32_t dst, const CUtensorMap* tm, int g, uint32_t bar) {
    asm volatile(
        "cp.async.bulk.tensor.4d.shared::cluster.global.mbarrier::complete_tx::bytes.multicast::cluster [%0], [%1, {%3, %3, %3, %4}], [%2], %5;" ::"r"(dst),
        "l"(tm), "r"(bar), "r"(0), "r"(g), "h"((uint16_t)3)
        : "memory");
}
__device__ __forceinline__ void tma_load_q(uint32_t dst, const CUtensorMap* tm, int g, int head, uint32_t bar) {
    asm volatile(
        "cp.async.bulk.tensor.5d.shared::cluster.global.mbarrier::complete_tx::bytes [%0], [%1, {%3, %3, %3, %4, %5}], [%2];" ::"r"(dst),
        "l"(tm), "r"(bar), "r"(0), "r"(g), "r"(head)
        : "memory");
}
__device__ __forceinline__ void tma_store_o(const CUtensorMap* tm, uint32_t src, int g, int head) {
    asm volatile("cp.async.bulk.tensor.5d.global.shared::cta.bulk_group [%0, {%2, %2, %2, %3, %4}], [%1];" ::"l"(tm),
                 "r"(src), "r"(0), "r"(g), "r"(head)
                 : "memory");
}
__device__ __forceinline__ void bulk_commit() { asm volatile("cp.async.bulk.commit_group;" ::: "memory"); }
__device__ __forceinline__ void bulk_wait_read() { asm volatile("cp.async.bulk.wait_group.read 0;" ::: "memory"); }
__device__ __forceinline__ void fence_async_smem() { asm volatile("fence.proxy.async.shared::cta;" ::: "memory"); }
__device__ __forceinline__ void stsm_x4(uint32_t addr, uint32_t r0, uint32_t r1, uint32_t r2, uint32_t r3) {
    asm volatile("stmatrix.sync.aligned.m8n8.x4.shared.b16 [%0], {%1, %2, %3, %4};" ::"r"(addr), "r"(r0), "r"(r1), "r"(r2), "r"(r3) : "memory");
}
__device__ __forceinline__ void ldsm_x4(uint32_t addr, uint32_t& r0, uint32_t& r1, uint32_t& r2, uint32_t& r3) {
    asm volatile("ldmatrix.sync.aligned.m8n8.x4.shared.b16 {%0, %1, %2, %3}, [%4];" : "=r"(r0), "=r"(r1), "=r"(r2), "=r"(r3) : "r"(addr) : "memory");
}
__device__ __forceinline__ void wgmma_fence() { asm volatile("wgmma.fence.sync.aligned;" ::: "memory"); }
__device__ __forceinline__ void wgmma_commit() { asm volatile("wgmma.commit_group.sync.aligned;" ::: "memory"); }
template <int N>
__device__ __forceinline__ void wgmma_wait() { asm volatile("wgmma.wait_group.sync.aligned %0;" ::"n"(N) : "memory"); }
__device__ __forceinline__ void bar_sync(int id, int n) { asm volatile("bar.sync %0, %1;" ::"r"(id), "r"(n) : "memory"); }
__device__ __forceinline__ void bar_arrive(int id, int n) { asm volatile("bar.arrive %0, %1;" ::"r"(id), "r"(n) : "memory"); }
__device__ __forceinline__ float ex2(float x) {
    float y;
    asm("ex2.approx.ftz.f32 %0, %1;" : "=f"(y) : "f"(x));
    return y;
}
__device__ __forceinline__ uint32_t pack_bf16(float lo, float hi) {
    uint32_t r;
    asm("cvt.rn.bf16x2.f32 %0, %1, %2;" : "=r"(r) : "f"(hi), "f"(lo));
    return r;
}
template <int N>
__device__ __forceinline__ void fence_regs(float (&r)[N]) {
#pragma unroll
    for (int i = 0; i < N; i++) asm volatile("" : "+f"(r[i])::"memory");
}
template <int N>
__device__ __forceinline__ void fence_regs(uint32_t (&r)[N]) {
#pragma unroll
    for (int i = 0; i < N; i++) asm volatile("" : "+r"(r[i])::"memory");
}
template <int N>
__device__ __forceinline__ void forget(float (&r)[N]) {
#pragma unroll
    for (int i = 0; i < N; i++) r[i] = 0.f;
}
__device__ __forceinline__ uint64_t make_desc(uint32_t lo, uint32_t hi) { return ((uint64_t)hi << 32) | lo; }
constexpr uint32_t DESC_HI = (GRP_BYTES >> 4) | (1u << 30);

__device__ __forceinline__ void wgmma_qk(float (&d)[32], uint32_t a0, uint32_t a1, uint32_t a2, uint32_t a3, uint64_t descB) {
    asm volatile(
        "{\n.reg .pred p;\n"
        "setp.eq.b32 p, 0, 0;\n"
        "wgmma.mma_async.sync.aligned.m64n64k16.f32.bf16.bf16 "
        "{%0, %1, %2, %3, %4, %5, %6, %7, %8, %9, %10, %11, %12, %13, %14, %15, "
        "%16, %17, %18, %19, %20, %21, %22, %23, %24, %25, %26, %27, %28, %29, %30, %31}, "
        "{%32, %33, %34, %35}, %36, p, 1, 1, 0;\n}\n"
        : "+f"(d[0]), "+f"(d[1]), "+f"(d[2]), "+f"(d[3]), "+f"(d[4]), "+f"(d[5]), "+f"(d[6]), "+f"(d[7]),
          "+f"(d[8]), "+f"(d[9]), "+f"(d[10]), "+f"(d[11]), "+f"(d[12]), "+f"(d[13]), "+f"(d[14]), "+f"(d[15]),
          "+f"(d[16]), "+f"(d[17]), "+f"(d[18]), "+f"(d[19]), "+f"(d[20]), "+f"(d[21]), "+f"(d[22]), "+f"(d[23]),
          "+f"(d[24]), "+f"(d[25]), "+f"(d[26]), "+f"(d[27]), "+f"(d[28]), "+f"(d[29]), "+f"(d[30]), "+f"(d[31])
        : "r"(a0), "r"(a1), "r"(a2), "r"(a3), "l"(descB));
}

__device__ __forceinline__ void wgmma_qk_init(float (&d)[32], uint32_t a0, uint32_t a1, uint32_t a2, uint32_t a3, uint64_t descB) {
    asm volatile(
        "{\n.reg .pred p;\n"
        "setp.ne.b32 p, 0, 0;\n"
        "wgmma.mma_async.sync.aligned.m64n64k16.f32.bf16.bf16 "
        "{%0, %1, %2, %3, %4, %5, %6, %7, %8, %9, %10, %11, %12, %13, %14, %15, "
        "%16, %17, %18, %19, %20, %21, %22, %23, %24, %25, %26, %27, %28, %29, %30, %31}, "
        "{%32, %33, %34, %35}, %36, p, 1, 1, 0;\n}\n"
        : "=f"(d[0]), "=f"(d[1]), "=f"(d[2]), "=f"(d[3]), "=f"(d[4]), "=f"(d[5]), "=f"(d[6]), "=f"(d[7]),
          "=f"(d[8]), "=f"(d[9]), "=f"(d[10]), "=f"(d[11]), "=f"(d[12]), "=f"(d[13]), "=f"(d[14]), "=f"(d[15]),
          "=f"(d[16]), "=f"(d[17]), "=f"(d[18]), "=f"(d[19]), "=f"(d[20]), "=f"(d[21]), "=f"(d[22]), "=f"(d[23]),
          "=f"(d[24]), "=f"(d[25]), "=f"(d[26]), "=f"(d[27]), "=f"(d[28]), "=f"(d[29]), "=f"(d[30]), "=f"(d[31])
        : "r"(a0), "r"(a1), "r"(a2), "r"(a3), "l"(descB));
}

__device__ __forceinline__ void wgmma_pv(float (&d)[96], uint32_t a0, uint32_t a1, uint32_t a2, uint32_t a3, uint64_t descB) {
    asm volatile(
        "{\n.reg .pred p;\n"
        "setp.eq.b32 p, 0, 0;\n"
        "wgmma.mma_async.sync.aligned.m64n192k16.f32.bf16.bf16 "
        "{%0, %1, %2, %3, %4, %5, %6, %7, %8, %9, %10, %11, %12, %13, %14, %15, "
        "%16, %17, %18, %19, %20, %21, %22, %23, %24, %25, %26, %27, %28, %29, %30, %31, "
        "%32, %33, %34, %35, %36, %37, %38, %39, %40, %41, %42, %43, %44, %45, %46, %47, "
        "%48, %49, %50, %51, %52, %53, %54, %55, %56, %57, %58, %59, %60, %61, %62, %63, "
        "%64, %65, %66, %67, %68, %69, %70, %71, %72, %73, %74, %75, %76, %77, %78, %79, "
        "%80, %81, %82, %83, %84, %85, %86, %87, %88, %89, %90, %91, %92, %93, %94, %95}, "
        "{%96, %97, %98, %99}, %100, p, 1, 1, 1;\n}\n"
        : "+f"(d[0]), "+f"(d[1]), "+f"(d[2]), "+f"(d[3]), "+f"(d[4]), "+f"(d[5]), "+f"(d[6]), "+f"(d[7]),
          "+f"(d[8]), "+f"(d[9]), "+f"(d[10]), "+f"(d[11]), "+f"(d[12]), "+f"(d[13]), "+f"(d[14]), "+f"(d[15]),
          "+f"(d[16]), "+f"(d[17]), "+f"(d[18]), "+f"(d[19]), "+f"(d[20]), "+f"(d[21]), "+f"(d[22]), "+f"(d[23]),
          "+f"(d[24]), "+f"(d[25]), "+f"(d[26]), "+f"(d[27]), "+f"(d[28]), "+f"(d[29]), "+f"(d[30]), "+f"(d[31]),
          "+f"(d[32]), "+f"(d[33]), "+f"(d[34]), "+f"(d[35]), "+f"(d[36]), "+f"(d[37]), "+f"(d[38]), "+f"(d[39]),
          "+f"(d[40]), "+f"(d[41]), "+f"(d[42]), "+f"(d[43]), "+f"(d[44]), "+f"(d[45]), "+f"(d[46]), "+f"(d[47]),
          "+f"(d[48]), "+f"(d[49]), "+f"(d[50]), "+f"(d[51]), "+f"(d[52]), "+f"(d[53]), "+f"(d[54]), "+f"(d[55]),
          "+f"(d[56]), "+f"(d[57]), "+f"(d[58]), "+f"(d[59]), "+f"(d[60]), "+f"(d[61]), "+f"(d[62]), "+f"(d[63]),
          "+f"(d[64]), "+f"(d[65]), "+f"(d[66]), "+f"(d[67]), "+f"(d[68]), "+f"(d[69]), "+f"(d[70]), "+f"(d[71]),
          "+f"(d[72]), "+f"(d[73]), "+f"(d[74]), "+f"(d[75]), "+f"(d[76]), "+f"(d[77]), "+f"(d[78]), "+f"(d[79]),
          "+f"(d[80]), "+f"(d[81]), "+f"(d[82]), "+f"(d[83]), "+f"(d[84]), "+f"(d[85]), "+f"(d[86]), "+f"(d[87]),
          "+f"(d[88]), "+f"(d[89]), "+f"(d[90]), "+f"(d[91]), "+f"(d[92]), "+f"(d[93]), "+f"(d[94]), "+f"(d[95])
        : "r"(a0), "r"(a1), "r"(a2), "r"(a3), "l"(descB));
}

__device__ __forceinline__ void wgmma_pv_init(float (&d)[96], uint32_t a0, uint32_t a1, uint32_t a2, uint32_t a3, uint64_t descB) {
    asm volatile(
        "{\n.reg .pred p;\n"
        "setp.ne.b32 p, 0, 0;\n"
        "wgmma.mma_async.sync.aligned.m64n192k16.f32.bf16.bf16 "
        "{%0, %1, %2, %3, %4, %5, %6, %7, %8, %9, %10, %11, %12, %13, %14, %15, "
        "%16, %17, %18, %19, %20, %21, %22, %23, %24, %25, %26, %27, %28, %29, %30, %31, "
        "%32, %33, %34, %35, %36, %37, %38, %39, %40, %41, %42, %43, %44, %45, %46, %47, "
        "%48, %49, %50, %51, %52, %53, %54, %55, %56, %57, %58, %59, %60, %61, %62, %63, "
        "%64, %65, %66, %67, %68, %69, %70, %71, %72, %73, %74, %75, %76, %77, %78, %79, "
        "%80, %81, %82, %83, %84, %85, %86, %87, %88, %89, %90, %91, %92, %93, %94, %95}, "
        "{%96, %97, %98, %99}, %100, p, 1, 1, 1;\n}\n"
        : "=f"(d[0]), "=f"(d[1]), "=f"(d[2]), "=f"(d[3]), "=f"(d[4]), "=f"(d[5]), "=f"(d[6]), "=f"(d[7]),
          "=f"(d[8]), "=f"(d[9]), "=f"(d[10]), "=f"(d[11]), "=f"(d[12]), "=f"(d[13]), "=f"(d[14]), "=f"(d[15]),
          "=f"(d[16]), "=f"(d[17]), "=f"(d[18]), "=f"(d[19]), "=f"(d[20]), "=f"(d[21]), "=f"(d[22]), "=f"(d[23]),
          "=f"(d[24]), "=f"(d[25]), "=f"(d[26]), "=f"(d[27]), "=f"(d[28]), "=f"(d[29]), "=f"(d[30]), "=f"(d[31]),
          "=f"(d[32]), "=f"(d[33]), "=f"(d[34]), "=f"(d[35]), "=f"(d[36]), "=f"(d[37]), "=f"(d[38]), "=f"(d[39]),
          "=f"(d[40]), "=f"(d[41]), "=f"(d[42]), "=f"(d[43]), "=f"(d[44]), "=f"(d[45]), "=f"(d[46]), "=f"(d[47]),
          "=f"(d[48]), "=f"(d[49]), "=f"(d[50]), "=f"(d[51]), "=f"(d[52]), "=f"(d[53]), "=f"(d[54]), "=f"(d[55]),
          "=f"(d[56]), "=f"(d[57]), "=f"(d[58]), "=f"(d[59]), "=f"(d[60]), "=f"(d[61]), "=f"(d[62]), "=f"(d[63]),
          "=f"(d[64]), "=f"(d[65]), "=f"(d[66]), "=f"(d[67]), "=f"(d[68]), "=f"(d[69]), "=f"(d[70]), "=f"(d[71]),
          "=f"(d[72]), "=f"(d[73]), "=f"(d[74]), "=f"(d[75]), "=f"(d[76]), "=f"(d[77]), "=f"(d[78]), "=f"(d[79]),
          "=f"(d[80]), "=f"(d[81]), "=f"(d[82]), "=f"(d[83]), "=f"(d[84]), "=f"(d[85]), "=f"(d[86]), "=f"(d[87]),
          "=f"(d[88]), "=f"(d[89]), "=f"(d[90]), "=f"(d[91]), "=f"(d[92]), "=f"(d[93]), "=f"(d[94]), "=f"(d[95])
        : "r"(a0), "r"(a1), "r"(a2), "r"(a3), "l"(descB));
}

__device__ __forceinline__ void wgmma_rk(float (&d)[8], uint64_t descA, uint64_t descB) {
    asm volatile(
        "{\n.reg .pred p;\n"
        "setp.eq.b32 p, 0, 0;\n"
        "wgmma.mma_async.sync.aligned.m64n16k16.f32.bf16.bf16 "
        "{%0, %1, %2, %3, %4, %5, %6, %7}, "
        "%8, %9, p, 1, 1, 0, 0;\n}\n"
        : "+f"(d[0]), "+f"(d[1]), "+f"(d[2]), "+f"(d[3]), "+f"(d[4]), "+f"(d[5]), "+f"(d[6]), "+f"(d[7])
        : "l"(descA), "l"(descB));
}

__device__ __forceinline__ void wgmma_rk_init(float (&d)[8], uint64_t descA, uint64_t descB) {
    asm volatile(
        "{\n.reg .pred p;\n"
        "setp.ne.b32 p, 0, 0;\n"
        "wgmma.mma_async.sync.aligned.m64n16k16.f32.bf16.bf16 "
        "{%0, %1, %2, %3, %4, %5, %6, %7}, "
        "%8, %9, p, 1, 1, 0, 0;\n}\n"
        : "=f"(d[0]), "=f"(d[1]), "=f"(d[2]), "=f"(d[3]), "=f"(d[4]), "=f"(d[5]), "=f"(d[6]), "=f"(d[7])
        : "l"(descA), "l"(descB));
}

__device__ __forceinline__ void wgmma_rv(float (&d)[8], uint64_t descA, uint64_t descB) {
    asm volatile(
        "{\n.reg .pred p;\n"
        "setp.eq.b32 p, 0, 0;\n"
        "wgmma.mma_async.sync.aligned.m64n16k16.f32.bf16.bf16 "
        "{%0, %1, %2, %3, %4, %5, %6, %7}, "
        "%8, %9, p, 1, 1, 1, 0;\n}\n"
        : "+f"(d[0]), "+f"(d[1]), "+f"(d[2]), "+f"(d[3]), "+f"(d[4]), "+f"(d[5]), "+f"(d[6]), "+f"(d[7])
        : "l"(descA), "l"(descB));
}

__device__ __forceinline__ void wgmma_rl(float (&d)[8], uint32_t a0, uint32_t a1, uint32_t a2, uint32_t a3, uint64_t descB) {
    asm volatile(
        "{\n.reg .pred p;\n"
        "setp.eq.b32 p, 0, 0;\n"
        "wgmma.mma_async.sync.aligned.m64n16k16.f32.bf16.bf16 "
        "{%0, %1, %2, %3, %4, %5, %6, %7}, "
        "{%8, %9, %10, %11}, %12, p, 1, 1, 0;\n}\n"
        : "+f"(d[0]), "+f"(d[1]), "+f"(d[2]), "+f"(d[3]), "+f"(d[4]), "+f"(d[5]), "+f"(d[6]), "+f"(d[7])
        : "r"(a0), "r"(a1), "r"(a2), "r"(a3), "l"(descB));
}

__device__ __forceinline__ void wgmma_rl_init(float (&d)[8], uint32_t a0, uint32_t a1, uint32_t a2, uint32_t a3, uint64_t descB) {
    asm volatile(
        "{\n.reg .pred p;\n"
        "setp.ne.b32 p, 0, 0;\n"
        "wgmma.mma_async.sync.aligned.m64n16k16.f32.bf16.bf16 "
        "{%0, %1, %2, %3, %4, %5, %6, %7}, "
        "{%8, %9, %10, %11}, %12, p, 1, 1, 0;\n}\n"
        : "=f"(d[0]), "=f"(d[1]), "=f"(d[2]), "=f"(d[3]), "=f"(d[4]), "=f"(d[5]), "=f"(d[6]), "=f"(d[7])
        : "r"(a0), "r"(a1), "r"(a2), "r"(a3), "l"(descB));
}


struct Item { int head; int grp; bool mc, rem; };
__device__ __forceinline__ Item decode_item(uint32_t e, int rank, int w) {
    Item it;
    it.mc = (e & 3) != 3;
    it.rem = !it.mc && (e >> 2 & 1) != w;
    it.head = it.mc ? e >> 2 : (e >> 3) * 2 + rank;
    it.grp = 32 * (e & 3) + (it.mc ? 16 * rank + 8 * w : it.rem ? 8 : 0);
    return it;
}
__device__ __forceinline__ uint32_t first_entry(uint32_t c) { return (c / 3) * 4 + c % 3; }

__device__ __forceinline__ uint32_t k_addr(int e) { return SM_K + ((e + KROT) & 3) * BLK_BYTES; }
__device__ __forceinline__ void next_v(uint32_t& v) { v = v == SM_V + 2 * BLK_BYTES ? SM_V : v + BLK_BYTES; }
__device__ __forceinline__ void wait_blocks(uint32_t sbase, int e) { mbar_wait(sbase + BAR_FULL + 8 * (e & 3), e >> 2 & 1); }
__device__ __forceinline__ uint64_t k_desc(int e) {
    return make_desc(((e + KROT) & 3) * (BLK_BYTES >> 4) + (((SM_BASE + SM_K) >> 4) | (1u << 16)), DESC_HI);
}
constexpr uint32_t V_DESC0 = ((SM_BASE + SM_V) >> 4) | ((SLAB_BYTES >> 4) << 16);
__device__ __forceinline__ void next_v_desc(uint32_t& v) { v = v == V_DESC0 + 2 * (BLK_BYTES >> 4) ? V_DESC0 : v + (BLK_BYTES >> 4); }
__device__ __forceinline__ constexpr uint32_t k_step(int k) { return (k & 3) == 3 ? (SLAB_BYTES >> 4) - 6 : 2; }

template <bool SPLIT>
__device__ __forceinline__ void issue_qk(float (&s)[32], uint32_t (&q)[48], int e) {
    fence_regs(q);
    wgmma_fence();
    uint64_t desc = k_desc(e);
#pragma unroll
    for (int k = 0; k < 12; k++) {
        if (k == 0) wgmma_qk_init(s, q[0], q[1], q[2], q[3], desc);
        else wgmma_qk(s, q[4 * k], q[4 * k + 1], q[4 * k + 2], q[4 * k + 3], desc);
        if (k < 11) desc += k_step(k);
        if (SPLIT && (k & 3) == 3) wgmma_commit();
    }
    if (!SPLIT) wgmma_commit();
}
template <bool FIRST, bool WAIT = true, bool FENCE = true>
__device__ __forceinline__ void issue_pv(float (&o)[96], uint32_t (&p)[16], uint32_t sbase, int b, uint32_t& v) {
    if (WAIT) wait_blocks(sbase, b + 2);
    if (!FIRST) fence_regs(o);
    fence_regs(p);
    if (FENCE) wgmma_fence();
    uint64_t desc = make_desc(v, DESC_HI);
#pragma unroll
    for (int k = 0; k < 4; k++) {
        if (FIRST && k == 0) wgmma_pv_init(o, p[0], p[1], p[2], p[3], desc);
        else wgmma_pv(o, p[4 * k], p[4 * k + 1], p[4 * k + 2], p[4 * k + 3], desc);
        if (k < 3) desc += 2 * GRP_BYTES >> 4;
    }
    wgmma_commit();
    next_v_desc(v);
}

__device__ __forceinline__ float opaque_copy(float x, uint32_t zero) { return x + __uint_as_float(zero); }

__device__ __forceinline__ float after(float x, float y, uint32_t zero) { return __uint_as_float(__float_as_uint(x) | (__float_as_uint(y) & zero)); }

template <bool FIRST>
__device__ __forceinline__ void exp_sum(float (&s)[32], float (&l)[2]) {
#pragma unroll
    for (int i = 0; i < 32; i++) s[i] = ex2(s[i]);
#pragma unroll
    for (int i = 0; i < 8; i++) {
        const float x = s[4 * i] + s[4 * i + 1], y = s[4 * i + 2] + s[4 * i + 3];
        if (FIRST && i == 0) { l[0] = x; l[1] = y; }
        else { l[0] += x; l[1] += y; }
    }
}
template <int LO, int HI>
__device__ __forceinline__ void exp_only(float (&s)[32]) {
#pragma unroll
    for (int i = LO; i < HI; i++) s[i] = ex2(s[i]);
}
__device__ __forceinline__ void sum_only(const float (&s)[32], float (&l)[2]) {
#pragma unroll
    for (int i = 0; i < 8; i++) { l[0] += s[4 * i] + s[4 * i + 1]; l[1] += s[4 * i + 2] + s[4 * i + 3]; }
}
__device__ __forceinline__ void pack_p(const float (&s)[32], uint32_t (&p)[16]) {
#pragma unroll
    for (int i = 0; i < 8; i++) {
        p[2 * i] = pack_bf16(s[4 * i], s[4 * i + 1]);
        p[2 * i + 1] = pack_bf16(s[4 * i + 2], s[4 * i + 3]);
    }
}
__device__ __forceinline__ bool sum_unsafe(float l) { return __float_as_uint(l) - SUM_LOW > SUM_HIGH - SUM_LOW; }

__device__ __forceinline__ void bb_boundary(uint32_t zero, float& x, float& y) {
    if (zero) {
#pragma unroll
        for (int i = 0; i < 12; i++) {
            asm volatile("mul.f32 %0, %0, %1;" : "+f"(x) : "f"(y));
            asm volatile("mul.f32 %0, %0, %1;" : "+f"(y) : "f"(x));
        }
    }
}
__device__ __forceinline__ void bb_boundary(uint32_t zero, float (&x)[2][2]) {
    if (zero) {
#pragma unroll
        for (int i = 0; i < 24; i++) asm volatile("mul.f32 %0, %0, %1;" : "+f"(x[i >> 1 & 1][i & 1]) : "f"(x[~i >> 1 & 1][i & 1]));
    }
}
__device__ __forceinline__ void bb_boundary(uint32_t zero, float (&x)[4]) {
    if (zero) {
#pragma unroll
        for (int i = 0; i < 24; i++) asm volatile("mul.f32 %0, %0, %1;" : "+f"(x[i & 3]) : "f"(x[(i + 2) & 3]));
    }
}
__device__ __forceinline__ uint32_t sched_fence() {
    uint32_t c;
    asm volatile("mov.u32 %0, %%clock;" : "=r"(c)::"memory");
    return c;
}
template <int CB>
__device__ __forceinline__ void load_q_slab(uint32_t (&q)[48], const uint32_t (&q_lane)[4]) {
#pragma unroll
    for (int k = 4 * CB; k < 4 * CB + 4; k++)
        ldsm_x4(q_lane[k & 3] + CB * SLAB_BYTES, q[4 * k], q[4 * k + 1], q[4 * k + 2], q[4 * k + 3]);
}
template <int LO, int HI, int STEP = 1>
__device__ __forceinline__ void scale_q(uint32_t (&q)[48]) {
#pragma unroll
    for (int i = LO; i < HI; i += STEP)
        asm("{\n.reg .b32 t;\nmul.rn.bf16x2 t, %0, %1;\nfma.rn.bf16x2 %0, %0, %2, t;\n}\n" : "+r"(q[i]) : "r"(SCALE_LO), "r"(SCALE_HI));
}
__device__ __forceinline__ void row_normalisers(float l0, float l1, float (&inv)[2][2], uint32_t& redo, uint32_t bit, uint32_t zero) {
    l0 += __shfl_xor_sync(0xffffffffu, l0, 1);
    l1 += __shfl_xor_sync(0xffffffffu, l1, 1);
    l0 += __shfl_xor_sync(0xffffffffu, l0, 2);
    l1 += __shfl_xor_sync(0xffffffffu, l1, 2);
    asm("rcp.approx.ftz.f32 %0, %1;" : "=f"(inv[0][0]) : "f"(l0));
    asm("rcp.approx.ftz.f32 %0, %1;" : "=f"(inv[1][0]) : "f"(l1));
    inv[0][1] = opaque_copy(inv[0][0], zero);
    inv[1][1] = opaque_copy(inv[1][0], zero);
    if (sum_unsafe(l0) | sum_unsafe(l1)) redo |= bit;
}
__device__ __forceinline__ void cvt_out(float (&o)[96], int k, const float (&inv)[2][2], uint32_t (&x)[4]) {
    float y[8];
#pragma unroll
    for (int i = 0; i < 8; i++) y[i] = o[8 * k + i] * inv[i >> 1 & 1][i & 1];
#pragma unroll
    for (int i = 0; i < 4; i++) x[i] = pack_bf16(y[2 * i], y[2 * i + 1]);
}
template <int K0, int K1, bool GAPS>
__device__ __forceinline__ void stage_output(float (&o)[96], const float (&inv)[2][2], const uint32_t (&q_lane)[4]) {
#pragma unroll
    for (int k = K0; k < K1; k++) {
        uint32_t x[4];
        cvt_out(o, k, inv, x);
        if (GAPS) wgmma_wait<0>();
        stsm_x4(q_lane[k & 3] + (k >> 2) * SLAB_BYTES, x[0], x[1], x[2], x[3]);
    }
}
template <int K0>
__device__ __forceinline__ void issue_qk_stage(float (&s)[32], uint32_t (&q)[48], int e, float (&o)[96], float (&inv)[2][2], const uint32_t (&q_lane)[4],
                                               uint32_t& keep) {
    constexpr int NS = 12 - K0;
    uint32_t x[NS][4];
#pragma unroll
    for (int j = 0; j < STG_N1; j++) cvt_out(o, K0 + j, inv, x[j]);
    fence_regs(q);
    wgmma_fence();
    uint64_t desc = k_desc(e);
#pragma unroll
    for (int k = 0; k < 12; k++) {
        if (k == 0) wgmma_qk_init(s, q[0], q[1], q[2], q[3], desc);
        else wgmma_qk(s, q[4 * k], q[4 * k + 1], q[4 * k + 2], q[4 * k + 3], desc);
        if (k < 11) desc += k_step(k);
        if (k == STG_CVTK) {
            keep &= sched_fence();
            fence_regs(inv[0]); fence_regs(inv[1]);
#pragma unroll
            for (int j = STG_N1; j < NS; j++) cvt_out(o, K0 + j, inv, x[j]);
        }
#pragma unroll
        for (int j = 0; j < NS; j++)
            if (k == (STG_POS >> 4 * j & 15)) stsm_x4(q_lane[(K0 + j) & 3] + ((K0 + j) >> 2) * SLAB_BYTES, x[j][0], x[j][1], x[j][2], x[j][3]);
    }
    wgmma_commit();
}
__device__ __forceinline__ void publish_output(uint32_t oready, int lane) {
    fence_async_smem();
    __syncwarp();
    mbar_arrive_pred(oready, lane == 0);
}

__device__ __forceinline__ void stsm_x4_t(uint32_t addr, uint32_t r0, uint32_t r1, uint32_t r2, uint32_t r3) {
    asm volatile("stmatrix.sync.aligned.m8n8.x4.trans.shared.b16 [%0], {%1, %2, %3, %4};" ::"r"(addr), "r"(r0), "r"(r1), "r"(r2), "r"(r3) : "memory");
}
__device__ __forceinline__ void issue_rem_qk(float (&s)[8], int e) {
    uint64_t da = k_desc(e), db = make_desc(((SM_BASE + SM_REM) >> 4) | (1u << 16), DESC_HI);
#pragma unroll
    for (int k = 0; k < 12; k++) {
        if (k == 0) wgmma_rk_init(s, da, db);
        else wgmma_rk(s, da, db);
        if (k < 11) { da += k_step(k); db += k_step(k); }
    }
    wgmma_commit();
}
constexpr uint32_t PT_DESC_HI = (1024 >> 4) | (1u << 30);
__device__ __forceinline__ void issue_rem_pv(float (&o)[3][8], uint32_t pt, uint32_t& v) {
    const uint64_t da = make_desc(v, DESC_HI), db = make_desc(pt * (2048 >> 4) + (((SM_BASE + SM_PT) >> 4) | (1u << 16)), PT_DESC_HI);
#pragma unroll
    for (int k = 0; k < 4; k++)
#pragma unroll
        for (int m = 0; m < 3; m++) wgmma_rv(o[m], da + k * (2 * GRP_BYTES >> 4) + m * (SLAB_BYTES >> 4), db + 2 * k);
    wgmma_commit();
    next_v_desc(v);
}
__device__ __forceinline__ void rem_softmax(float (&s)[8], float (&l)[4]) {
#pragma unroll
    for (int i = 0; i < 8; i++) s[i] = ex2(s[i] * SCALE_LOG2E);
    l[0] += s[0] + s[2]; l[1] += s[1] + s[3]; l[2] += s[4] + s[6]; l[3] += s[5] + s[7];
}
__device__ __forceinline__ void rem_store(const float (&s)[8], uint32_t addr) {
    stsm_x4_t(addr, pack_bf16(s[0], s[1]), pack_bf16(s[2], s[3]), pack_bf16(s[4], s[5]), pack_bf16(s[6], s[7]));
}

__device__ __forceinline__ void mma_16816(float (&c)[4], uint32_t a0, uint32_t a1, uint32_t a2, uint32_t a3, uint32_t b0, uint32_t b1) {
    asm volatile("mma.sync.aligned.m16n8k16.row.col.f32.bf16.bf16.f32 {%0, %1, %2, %3}, {%4, %5, %6, %7}, {%8, %9}, {%0, %1, %2, %3};"
                 : "+f"(c[0]), "+f"(c[1]), "+f"(c[2]), "+f"(c[3]) : "r"(a0), "r"(a1), "r"(a2), "r"(a3), "r"(b0), "r"(b1));
}
__device__ __forceinline__ void exact_rows(const uint4* __restrict__ gq, const uint4* __restrict__ gk, const uint4* __restrict__ gv, uint4* __restrict__ go,
                                           int head, int row0, int lane) {
    constexpr int R = ROW_BYTES / 16;
    const int g = lane >> 2, c = lane & 3;
    const uint4* pq = gq + ((size_t)head * SQ + row0 + g) * R + c;
    uint4 qa[6], qb[6];
#pragma unroll
    for (int k = 0; k < 6; k++) { qa[k] = __ldg(pq + 4 * k); qb[k] = __ldg(pq + 8 * R + 4 * k); }
    float o[24][4], m[2] = {-INFINITY, -INFINITY}, l[2] = {0.f, 0.f};
#pragma unroll
    for (int i = 0; i < 24; i++) o[i][0] = o[i][1] = o[i][2] = o[i][3] = 0.f;
#pragma unroll 1
    for (int key0 = 0; key0 < SK; key0 += 16) {
        float s[2][4];
#pragma unroll
        for (int j = 0; j < 2; j++) {
            s[j][0] = s[j][1] = s[j][2] = s[j][3] = 0.f;
            const uint4* pk = gk + ((size_t)head * SK + key0 + 8 * j + g) * R + c;
#pragma unroll
            for (int k = 0; k < 6; k++) {
                const uint4 x = __ldg(pk + 4 * k);
                mma_16816(s[j], qa[k].x, qb[k].x, qa[k].y, qb[k].y, x.x, x.y);
                mma_16816(s[j], qa[k].z, qb[k].z, qa[k].w, qb[k].w, x.z, x.w);
            }
        }
#pragma unroll
        for (int h = 0; h < 2; h++) {
            float f = fmaxf(fmaxf(s[0][2 * h], s[0][2 * h + 1]), fmaxf(s[1][2 * h], s[1][2 * h + 1]));
            f = fmaxf(f, __shfl_xor_sync(0xffffffffu, f, 1));
            f = fmaxf(f, __shfl_xor_sync(0xffffffffu, f, 2));
            f = fmaxf(f, m[h]);
            const float ref = f == -INFINITY ? 0.f : f;
            const float sc = ex2((m[h] - ref) * SCALE_LOG2E);
            m[h] = f;
            l[h] *= sc;
#pragma unroll
            for (int j = 0; j < 2; j++)
#pragma unroll
                for (int e = 0; e < 2; e++) { s[j][2 * h + e] = ex2((s[j][2 * h + e] - ref) * SCALE_LOG2E); l[h] += s[j][2 * h + e]; }
#pragma unroll
            for (int i = 0; i < 24; i++) { o[i][2 * h] *= sc; o[i][2 * h + 1] *= sc; }
        }
        const uint32_t a0 = pack_bf16(s[0][0], s[0][1]), a1 = pack_bf16(s[0][2], s[0][3]), a2 = pack_bf16(s[1][0], s[1][1]), a3 = pack_bf16(s[1][2], s[1][3]);
        const uint4* pv = gv + ((size_t)head * SK + key0 + 2 * c) * R + g;
#pragma unroll
        for (int sl = 0; sl < 3; sl++) {
            const uint4 v0 = __ldg(pv + 8 * sl), v1 = __ldg(pv + R + 8 * sl), v2 = __ldg(pv + 8 * R + 8 * sl), v3 = __ldg(pv + 9 * R + 8 * sl);
            const uint32_t w0[4] = {v0.x, v0.y, v0.z, v0.w}, w1[4] = {v1.x, v1.y, v1.z, v1.w}, w2[4] = {v2.x, v2.y, v2.z, v2.w}, w3[4] = {v3.x, v3.y, v3.z, v3.w};
#pragma unroll
            for (int i = 0; i < 8; i++)
                mma_16816(o[8 * sl + i], a0, a1, a2, a3, __byte_perm(w0[i >> 1], w1[i >> 1], (i & 1) ? 0x7632 : 0x5410),
                          __byte_perm(w2[i >> 1], w3[i >> 1], (i & 1) ? 0x7632 : 0x5410));
        }
    }
#pragma unroll
    for (int h = 0; h < 2; h++) {
        l[h] += __shfl_xor_sync(0xffffffffu, l[h], 1);
        l[h] += __shfl_xor_sync(0xffffffffu, l[h], 2);
        const float inv = 1.0f / l[h];
        uint4* po = go + ((size_t)head * SQ + row0 + 8 * h + g) * R + 2 * c;
#pragma unroll
        for (int sl = 0; sl < 3; sl++)
#pragma unroll
            for (int e = 0; e < 2; e++) {
                uint32_t w[4];
#pragma unroll
                for (int i = 0; i < 4; i++) w[i] = pack_bf16(o[8 * sl + 2 * i][2 * h + e] * inv, o[8 * sl + 2 * i + 1][2 * h + e] * inv);
                po[8 * sl + e] = make_uint4(w[0], w[1], w[2], w[3]);
            }
    }
}

#define ROLE_SETUP()                                                                          \
    uint32_t bid_;                                                                            \
    asm volatile("mov.u32 %0, %%ctaid.x;" : "=r"(bid_));                                      \
    const uint32_t rank = bid_ & 1;                                                           \
    const int cluster_id = bid_ >> 1;                                                         \
    const uint16_t* sched = SCHED[cluster_id];

__device__ __forceinline__ void consumer(const uint32_t sbase, const int warp_idx, const int lane, const uint32_t zero, const uint4* __restrict__ gq,
                                         const uint4* __restrict__ gk, const uint4* __restrict__ gv, uint4* __restrict__ go) {
    ROLE_SETUP()
    const int wg = (warp_idx >> 2) - 1;
    const int tw = threadIdx.x & 127;
    const int bar_me = __shfl_sync(0xffffffffu, 1 + wg + (lane & zero), lane), bar_other = __shfl_sync(0xffffffffu, 2 - wg + (lane & zero), lane);
    const uint32_t qo = sbase + SM_QO + wg * BLK_BYTES + (warp_idx & 3) * 2 * GRP_BYTES;
    uint32_t q_lane[4];
#pragma unroll
    for (int i = 0; i < 4; i++)
        q_lane[i] = __shfl_sync(0xffffffffu, (qo + (lane & 7) * 128 + ((lane >> 3) & 1) * GRP_BYTES + (((lane >> 4) ^ (lane & 7)) << 4)) ^ (i * 32), lane);
    const uint32_t qfull = sbase + BAR_QFULL + 8 * wg, oready = sbase + BAR_OREADY + 8 * wg;

    float o[96], s[32], l[2];
    uint32_t q[48], p[16];
    uint32_t redo = 0;
    uint32_t v = V_DESC0;
    const uint32_t rel_pred = (tw == 0 || tw == 32) ? 1u : 0u;
    const uint32_t rel_base = __shfl_sync(0xffffffffu, mapa(sbase, warp_idx & 1) + BAR_DONE, 0);
    auto release = [&](int e) { mbar_arrive_cluster_pred(rel_base + 8 * (e & 3), rel_pred); };

    if (wg == 1) bar_arrive(1, 256);

    mbar_wait(qfull, 0);
    load_q_slab<0>(q, q_lane); load_q_slab<1>(q, q_lane); load_q_slab<2>(q, q_lane);
    scale_q<0, 48>(q);
    wait_blocks(sbase, 0);
    bar_sync(bar_me, 256);
    issue_qk<false>(s, q, 0);
    bar_arrive(bar_other, 256);
    const int n_items = sched[SCHED_COUNT];
    const uint32_t breaks = __shfl_sync(0xffffffffu, reinterpret_cast<const uint32_t*>(sched + SCHED_BREAKS)[wg], 0);
    wgmma_wait<0>();
    fence_regs(s);
    release(0);
    exp_sum<true>(s, l);
    pack_p(s, p);
    wait_blocks(sbase, 1);
    wait_blocks(sbase, 2);
    float inv[2][2] = {{0.f, 0.f}, {0.f, 0.f}};
    forget(o);

    auto phase_tail = [&](int b) {
        exp_sum<false>(s, l);
        fence_regs(s);
        mbar_wait(sbase + BAR_DUMMY, 1);
        wgmma_wait<0>();
        fence_regs(o);
        fence_regs(p);
        release(b + 1);
        pack_p(s, p);
    };

    for (int t = 0;; t++) {
        const bool has_next = t + 1 < n_items, chain = !(breaks >> t & 2);
        bar_sync(bar_me, 256);
        uint32_t keep = zero;
        issue_qk_stage<STAGE_SPLIT>(s, q, 1, o, inv, q_lane, keep);
        issue_pv<true, false>(o, p, sbase, 0, v);
        bar_arrive(bar_other, 256);
        wgmma_wait<1>();
        fence_regs(s);
        phase_tail(0);
        redo |= keep & p[15];
#pragma unroll 1
        for (int b = 1; b < NBLK - 2; b++) {
            bar_sync(bar_me, 256);
            issue_qk<false>(s, q, b + 1);
            if (b == PUB_B) publish_output(oready, lane);
            issue_pv<false>(o, p, sbase, b, v);
            bar_arrive(bar_other, 256);
            wgmma_wait<1>();
            fence_regs(s);
            phase_tail(b);
        }
        uint32_t c[8];
        mbar_wait(qfull, ~t & 1);
        bar_sync(bar_me, 256);
        issue_qk<true>(s, q, 7);
        wait_blocks(sbase, 8);
        wgmma_wait<2>();
        load_q_slab<0>(q, q_lane);
        issue_pv<false, false>(o, p, sbase, 6, v);
        bar_arrive(bar_other, 256);
        c[0] = sched_fence();
        wgmma_wait<2>();
        scale_q<0, 16, 4>(q);
        fence_regs(q);
        c[1] = sched_fence();
        load_q_slab<1>(q, q_lane);
        c[2] = sched_fence();
        wgmma_wait<1>();
        fence_regs(s);
        exp_only<0, P6N>(s);
        scale_q<1, 16, 4>(q); scale_q<2, 16, 4>(q); scale_q<3, 16, 4>(q);
        fence_regs(s); fence_regs(q);
        c[3] = sched_fence();
        scale_q<16, 32, 4>(q);
        fence_regs(q);
        c[4] = sched_fence();
        load_q_slab<2>(q, q_lane);
        c[5] = sched_fence();
        uint32_t p7[16];
        exp_only<P6N, 32>(s);
        scale_q<17, 32, 4>(q); scale_q<18, 32, 4>(q); scale_q<19, 32, 4>(q);
        fence_regs(s); fence_regs(q); fence_regs(l);
        c[6] = sched_fence();
        wgmma_wait<0>();
        fence_regs(o);
        fence_regs(p);
        release(7);
        sum_only(s, l);
        pack_p(s, p7);
        fence_regs(p7);
        c[7] = sched_fence();
        scale_q<32, 48>(q);
        redo |= c[0] & c[1] & c[2] & c[3] & c[4] & c[5] & c[6] & c[7] & zero;
        if (chain) {
            bar_sync(bar_me, 256);
            issue_qk<false>(s, q, 0);
            issue_pv<false>(o, p7, sbase, 7, v);
            bar_arrive(bar_other, 256);
            wgmma_wait<1>();
            fence_regs(s);
            row_normalisers(after(l[0], s[30], zero), after(l[1], s[31], zero), inv, redo, 1u << t, zero);
            exp_sum<true>(s, l);
            pack_p(s, p);
            fence_regs(p);
            fence_regs(s); fence_regs(l);
            wait_blocks(sbase, 10);
            wgmma_wait<0>();
            fence_regs(o);
            fence_regs(p7);
            release(8);
            stage_output<0, STAGE_SPLIT, true>(o, inv, q_lane);
            continue;
        }
        if (!has_next) {
            bar_sync(bar_me, 256);
            issue_pv<false>(o, p7, sbase, 7, v);
            if ((int)breaks < 0) bar_arrive(bar_other, 256);
            row_normalisers(l[0], l[1], inv, redo, 1u << t, zero);
            wgmma_wait<0>();
            fence_regs(o);
            stage_output<0, 12, true>(o, inv, q_lane);
            break;
        }
        float rs[8], rs0[8];
        bar_sync(bar_me, 256);
        fence_regs(o); fence_regs(p7);
        wgmma_fence();
        issue_rem_qk(rs0, 0);
        issue_pv<false, false, false>(o, p7, sbase, 7, v);
        issue_rem_qk(rs, 1);
        bar_arrive(bar_other, 256);
        const uint32_t t_lane = sbase + (lane & 7) * 128 + ((((warp_idx & 3) * 2 + (lane >> 3 & 1)) ^ (lane & 7)) << 4);
        const uint32_t pt_lane = t_lane + SM_PT + (lane >> 4) * 1024;
        float ro[3][8], rl[4] = {0.f, 0.f, 0.f, 0.f};
        bb_boundary(zero, l[0], l[1]);
        row_normalisers(l[0], l[1], inv, redo, 1u << t, zero);
        t++;
        bb_boundary(zero, inv);
        wgmma_wait<1>();
        fence_regs(rs0); fence_regs(o);
        release(0);
        rem_softmax(rs0, rl);
        rem_store(rs0, pt_lane);
        bb_boundary(zero, rl);
        wgmma_wait<0>();
        fence_regs(rs);
        rem_softmax(rs, rl);
        rem_store(rs, pt_lane + 2048);
        fence_async_smem();
        mbar_arrive_pred(qfull, tw == 0);
#pragma unroll
        for (int i = 0; i < 8; i++) ro[0][i] = ro[1][i] = ro[2][i] = 0.f;
#pragma unroll 1
        for (int b = 0;; b++) {
            bar_sync(bar_me, 256);
            fence_regs(ro[0]); fence_regs(ro[1]); fence_regs(ro[2]);
            wgmma_fence();
            issue_rem_qk(rs, b + 2);
            issue_rem_pv(ro, b & 1, v);
            bar_arrive(bar_other, 256);
            wgmma_wait<1>();
            fence_regs(rs);
            rem_softmax(rs, rl);
            fence_regs(rs);
            bb_boundary(zero, rl[0], rl[1]);
            wgmma_wait<0>();
            fence_regs(ro[0]); fence_regs(ro[1]); fence_regs(ro[2]);
            release(b + 1);
            bar_sync(3, 128);
            rem_store(rs, pt_lane + (b & 1) * 2048);
            if (b == NBLK - 3) break;
            fence_async_smem();
            if (b == MS0) stage_output<0, STAGE_SPLIT / 4, false>(o, inv, q_lane);
            if (b == MS0 + 1) stage_output<STAGE_SPLIT / 4, STAGE_SPLIT / 2, false>(o, inv, q_lane);
            if (b == MS0 + 2) stage_output<STAGE_SPLIT / 2, STAGE_SPLIT * 3 / 4, false>(o, inv, q_lane);
            if (b == MS0 + 3) stage_output<STAGE_SPLIT * 3 / 4, STAGE_SPLIT, false>(o, inv, q_lane);
        }
        {
            const uint32_t h0 = pack_bf16(rl[0], rl[1]), h1 = pack_bf16(rl[2], rl[3]);
            stsm_x4_t(pt_lane + (SM_REM - SM_PT), h0, pack_bf16(rl[0] - __uint_as_float(h0 << 16), rl[1] - __uint_as_float(h0 & 0xffff0000u)),
                      h1, pack_bf16(rl[2] - __uint_as_float(h1 << 16), rl[3] - __uint_as_float(h1 & 0xffff0000u)));
        }
        fence_async_smem();
        uint32_t ones[4] = {0x3F803F80u, 0x3F803F80u, 0x3F803F80u, 0x3F803F80u};
        auto rem_last = [&]() {
            wgmma_commit();
            issue_rem_pv(ro, 0, v);
            wait_blocks(sbase, 9);
            fence_regs(ro[0]); fence_regs(ro[1]); fence_regs(ro[2]);
            wgmma_fence();
            issue_rem_pv(ro, 1, v);
            bar_arrive(bar_other, 256);
            wgmma_wait<2>();
            fence_regs(rs);
            mbar_arrive_pred(sbase + BAR_SUMS, lane == 0);
            if (sum_unsafe(rs[0]) | sum_unsafe(rs[1]) | sum_unsafe(rs[4]) | sum_unsafe(rs[5])) redo |= 1u << t;
#pragma unroll
            for (int i = 0; i < 4; i++) asm("rcp.approx.ftz.f32 %0, %1;" : "=f"(rl[i]) : "f"(rs[(i & 2) * 2 + (i & 1)]));
        };
        auto rem_stage = [&]() {
            mbar_wait(sbase + BAR_SUMS, wg ^ 1);
            wgmma_wait<0>();
            fence_regs(ro[0]); fence_regs(ro[1]); fence_regs(ro[2]);
            release(7);
            release(0);
#pragma unroll
            for (int m = 0; m < 3; m++)
                stsm_x4_t(t_lane + SM_REM + (lane >> 4) * GRP_BYTES + m * SLAB_BYTES, pack_bf16(ro[m][0] * rl[0], ro[m][1] * rl[1]), pack_bf16(ro[m][2] * rl[0], ro[m][3] * rl[1]),
                          pack_bf16(ro[m][4] * rl[2], ro[m][5] * rl[3]), pack_bf16(ro[m][6] * rl[2], ro[m][7] * rl[3]));
        };
        const uint64_t sum_desc = make_desc(((SM_BASE + SM_REM) >> 4) | (1u << 16), PT_DESC_HI);
        fence_regs(ones);
        bar_sync(bar_me, 256);
        fence_regs(ro[0]); fence_regs(ro[1]); fence_regs(ro[2]);
        if (t + 1 == n_items) {
            wgmma_fence();
            wgmma_rl_init(rs, ones[0], ones[1], ones[2], ones[3], sum_desc);
#pragma unroll
            for (int k = 1; k < 4; k++) wgmma_rl(rs, ones[0], ones[1], ones[2], ones[3], sum_desc + 2 * k);
            rem_last();
            stage_output<STAGE_SPLIT, 12, false>(o, inv, q_lane);
            rem_stage();
            break;
        }
        fence_regs(q);
        wgmma_fence();
        {
            uint64_t desc = k_desc(0);
#pragma unroll
            for (int k = 0; k < 12; k++) {
                if (k == 0) wgmma_qk_init(s, q[0], q[1], q[2], q[3], desc);
                else wgmma_qk(s, q[4 * k], q[4 * k + 1], q[4 * k + 2], q[4 * k + 3], desc);
                if (k < 11) desc += k_step(k);
                if (k == SK0) wgmma_rl_init(rs, ones[0], ones[1], ones[2], ones[3], sum_desc);
#pragma unroll
                for (int j = 1; j < 4; j++)
                    if (k == SK0 + j * SDK) wgmma_rl(rs, ones[0], ones[1], ones[2], ones[3], sum_desc + 2 * j);
            }
        }
        rem_last();
        fence_regs(s);
        exp_sum<true>(s, l);
        pack_p(s, p);
        rem_stage();
        wait_blocks(sbase, 2);
    }
    redo = __reduce_or_sync(0xffffffffu, redo);
    if (redo) asm volatile("st.shared.u32 [%0], %1;" ::"r"(sbase + SM_REDO + 4 * wg), "r"(1) : "memory");
    publish_output(oready, lane);
    if (redo) {
        mbar_wait(sbase + BAR_STORED + 8 * wg, 0);
        asm volatile("fence.proxy.async;" ::: "memory");
        for (; redo; redo &= redo - 1) {
            const Item it = decode_item(sched[__ffs(redo) - 1], rank, wg);
            const int row0 = it.grp * 8 + (warp_idx & 3) * 16;
            if (row0 < SQ) exact_rows(gq, gk, gv, go, it.head, row0, lane);
        }
    }
}

__global__ void __cluster_dims__(2, 1, 1) __launch_bounds__(384, 1)
attn_fwd_kernel(const __grid_constant__ CUtensorMap tmQ, const __grid_constant__ CUtensorMap tmK, const __grid_constant__ CUtensorMap tmV,
                const __grid_constant__ CUtensorMap tmO, const __grid_constant__ CUtensorMap tmR, const uint32_t zero,
                const uint4* __restrict__ gq, const uint4* __restrict__ gk, const uint4* __restrict__ gv, uint4* __restrict__ go) {
    extern __shared__ __align__(1024) uint8_t smem_raw[];
    const uint32_t sbase = smem_u32(smem_raw);
    const int warp_idx = __shfl_sync(0xffffffffu, threadIdx.x >> 5, 0);
    const int lane = threadIdx.x & 31;

    if (threadIdx.x == 0) {
        if ((sbase & 0x3FFFF) != SM_BASE) __trap();
        for (int i = 0; i < 4; i++) { mbar_init(sbase + BAR_FULL + 8 * i, 1); mbar_init(sbase + BAR_DONE + 8 * i, 4); }
        for (int i = 0; i < 2; i++) { mbar_init(sbase + BAR_QFULL + 8 * i, 1); mbar_init(sbase + BAR_OREADY + 8 * i, 4); mbar_init(sbase + BAR_STORED + 8 * i, 1); }
        mbar_init(sbase + BAR_DUMMY, 1);
        mbar_init(sbase + BAR_REMFREE, 1);
        mbar_init(sbase + BAR_SUMS, 4);
        asm volatile("st.shared.v2.u32 [%0], {%1, %1};" ::"r"(sbase + SM_REDO), "r"(0) : "memory");
        asm volatile("fence.mbarrier_init.release.cluster;" ::: "memory");
    } else if (threadIdx.x == 32) {
        asm volatile("prefetch.tensormap [%0];" ::"l"(&tmQ) : "memory");
        asm volatile("prefetch.tensormap [%0];" ::"l"(&tmK) : "memory");
        asm volatile("prefetch.tensormap [%0];" ::"l"(&tmV) : "memory");
        asm volatile("prefetch.tensormap [%0];" ::"l"(&tmO) : "memory");
        asm volatile("prefetch.tensormap [%0];" ::"l"(&tmR) : "memory");
    }
    __syncthreads();
    asm volatile("barrier.cluster.arrive.relaxed.aligned;" ::: "memory");
    if (warp_idx < 3 && (int)(blockIdx.x >> 1) < EARLY_CLUSTERS) {
        if (elect_one()) {
            const int w = warp_idx - 1;
            const Item q = decode_item(first_entry(blockIdx.x >> 1), blockIdx.x & 1, w);
            if (warp_idx == 0) {
                mbar_expect_tx(sbase + BAR_FULL, BLK_BYTES);
                tma_load_kv(sbase + k_addr(0), &tmK, q.head * (SK / 8), sbase + BAR_FULL);
            } else {
                mbar_expect_tx(sbase + BAR_QFULL + 8 * w, BLK_BYTES);
                tma_load_q(sbase + SM_QO + w * BLK_BYTES, &tmQ, q.grp, q.head, sbase + BAR_QFULL + 8 * w);
            }
        }
        __syncwarp();
    }
    asm volatile("barrier.cluster.wait.aligned;" ::: "memory");

    if (warp_idx < 4) {
        asm volatile("setmaxnreg.dec.sync.aligned.u32 %0;" ::"n"(PRODUCER_REGS));
        ROLE_SETUP()
        if (cluster_id >= EARLY_CLUSTERS) {
            const uint32_t t0 = clock(), d = (cluster_id - EARLY_CLUSTERS + 1) * START_STEP;
            while ((uint32_t)clock() - t0 < d) __nanosleep(20);
        }
        if (warp_idx == 0) {
            if (elect_one()) {
                auto load = [&](const CUtensorMap* tm, uint32_t owner, const Item& it, int blk, uint32_t dst, uint32_t full) {
                    const int grp = it.head * (SK / 8) + blk * 8;
                    if (!it.mc) tma_load_kv(sbase + dst, tm, grp, full);
                    else if (rank == owner) tma_load_kv_mc(sbase + dst, tm, grp, full);
                };
                Item iv = decode_item(first_entry(cluster_id), rank, 0), ik = iv;
                for (int e = cluster_id < EARLY_CLUSTERS; e < 2; e++) {
                    mbar_expect_tx(sbase + BAR_FULL + 8 * e, BLK_BYTES);
                    load(&tmK, 0, ik, e, k_addr(e), sbase + BAR_FULL + 8 * e);
                }
                uint32_t v = SM_V;
                bool more = true;
                for (int t = 1; more; t++) {
#pragma unroll 1
                    for (int e = 2; e < NBLK + 2; e++) {
                        if (e == NBLK) { more = t < sched[SCHED_COUNT]; ik = decode_item(sched[t], rank, 0); }
                        const uint32_t full = sbase + BAR_FULL + 8 * (e & 3);
                        mbar_sleep(full + (BAR_DONE - BAR_FULL), ~e >> 2 & 1);
                        mbar_expect_tx(full, more ? 2 * BLK_BYTES : BLK_BYTES);
                        load(&tmV, 1, iv, e - 2, v, full);
                        if (more) load(&tmK, 0, ik, e & 7, k_addr(e), full);
                        next_v(v);
                    }
                    iv = ik;
                }
            }
        } else if (warp_idx < 3) {
            if (elect_one()) {
                const int w = warp_idx - 1;
                const uint32_t buf = sbase + SM_QO + w * BLK_BYTES;
                const uint32_t qfull = sbase + BAR_QFULL + 8 * w, oready = sbase + BAR_OREADY + 8 * w;
                if (cluster_id >= EARLY_CLUSTERS) {
                    const Item q = decode_item(first_entry(cluster_id), rank, w);
                    mbar_expect_tx(qfull, BLK_BYTES);
                    tma_load_q(buf, &tmQ, q.grp, q.head, qfull);
                }
                const int n_items = sched[SCHED_COUNT];
                for (int r = 0, phase = 0; r <= n_items; r++, phase ^= 1) {
                    const Item rq = decode_item(sched[r + 1], rank, w), q = decode_item(sched[r + 1 + rq.rem], rank, w);
                    const Item ro = decode_item(sched[r > 0 ? r - 1 : 0], rank, w), o = decode_item(sched[r > 0 ? r - 1 - ro.rem : 0], rank, w);
                    mbar_sleep(oready, phase);
                    if (r > 0) {
                        tma_store_o(&tmO, buf, o.grp, o.head);
                        if (ro.rem) tma_store_o(&tmO, sbase + SM_REM, ro.grp, ro.head);
                        bulk_commit();
                        bulk_wait_read();
                        if (ro.rem) mbar_arrive(sbase + BAR_REMFREE);
                    }
                    if (r < n_items) {
                        const bool full = r + 1 + rq.rem < n_items;
                        mbar_expect_tx(qfull, (rq.rem ? REM_BYTES : 0) + (full ? BLK_BYTES : 0));
                        if (full) tma_load_q(buf, &tmQ, q.grp, q.head, qfull);
                        if (rq.rem) {
                            mbar_sleep(sbase + BAR_REMFREE, w);
                            tma_load_q(sbase + SM_REM, &tmR, rq.grp, rq.head, qfull);
                        }
                        r += rq.rem;
                    }
                }
                uint32_t redo;
                asm volatile("ld.shared.u32 %0, [%1];" : "=r"(redo) : "r"(sbase + SM_REDO + 4 * w) : "memory");
                if (redo) {
                    asm volatile("cp.async.bulk.wait_group 0;\nfence.proxy.async;" ::: "memory");
                    mbar_arrive(sbase + BAR_STORED + 8 * w);
                }
            }
        }
        else if (T_KVPF && elect_one()) {
            const int n_items = sched[SCHED_COUNT];
            const char* kv = reinterpret_cast<const char*>(rank ? gv : gk);
#pragma unroll 1
            for (int e = 4; e < NBLK * n_items; e++) {
                mbar_sleep(sbase + BAR_DONE + 8 * (e & 3), ~e >> 2 & 1);
                const int x = e + T_KVPF - 2 * rank;
                const uint32_t it = sched[x >> 3];
                if (x >> 3 < n_items && (it & 3) != 3)
                    asm volatile("cp.async.bulk.prefetch.L2.global [%0], %1;" ::"l"(kv + ((it >> 2) * 24 + (x & 7) * 3 + (it & 3)) * (BLK_BYTES / 3)), "r"(BLK_BYTES / 3) : "memory");
            }
        }
    } else {
        asm volatile("setmaxnreg.inc.sync.aligned.u32 %0;" ::"n"(CONSUMER_REGS));
        consumer(sbase, warp_idx, lane, zero, gq, gk, gv, go);
    }
    asm volatile("barrier.cluster.arrive.relaxed.aligned;\nbarrier.cluster.wait.aligned;" ::: "memory");
}

typedef CUresult (*EncodeTiledFn)(CUtensorMap*, CUtensorMapDataType, cuuint32_t, void*, const cuuint64_t*, const cuuint64_t*,
                                  const cuuint32_t*, const cuuint32_t*, CUtensorMapInterleave, CUtensorMapSwizzle,
                                  CUtensorMapL2promotion, CUtensorMapFloatOOBfill);

}

extern "C" void kernel_launch(void* const* d_in, const int* in_sizes, int n_in, void* d_out, int out_size) {
    (void)in_sizes; (void)n_in; (void)out_size;
    static CUtensorMap tmQ, tmK, tmV, tmO, tmR;
    static void* cached[4] = {nullptr, nullptr, nullptr, nullptr};
    if (cached[0] != d_in[0] || cached[1] != d_in[1] || cached[2] != d_in[2] || cached[3] != d_out) {
        void* fn = nullptr;
        cudaDriverEntryPointQueryResult qr;
        cudaGetDriverEntryPoint("cuTensorMapEncodeTiled", &fn, cudaEnableDefault, &qr);
        EncodeTiledFn enc = (EncodeTiledFn)fn;
        const cuuint32_t es[5] = {1, 1, 1, 1, 1};
        const cuuint32_t box[5] = {64, 8, 3, 8, 1};
        const cuuint32_t box_rem[5] = {64, 8, 3, 2, 1};
        {
            cuuint64_t gd[5] = {64, 8, 3, SQ / 8, NHEADS};
            cuuint64_t gs[4] = {ROW_BYTES, 128, 8 * ROW_BYTES, (cuuint64_t)SQ * ROW_BYTES};
            enc(&tmQ, CU_TENSOR_MAP_DATA_TYPE_BFLOAT16, 5, d_in[0], gd, gs, box, es, CU_TENSOR_MAP_INTERLEAVE_NONE,
                CU_TENSOR_MAP_SWIZZLE_128B, CU_TENSOR_MAP_L2_PROMOTION_NONE, CU_TENSOR_MAP_FLOAT_OOB_FILL_NONE);
            enc(&tmR, CU_TENSOR_MAP_DATA_TYPE_BFLOAT16, 5, d_in[0], gd, gs, box_rem, es, CU_TENSOR_MAP_INTERLEAVE_NONE,
                CU_TENSOR_MAP_SWIZZLE_128B, CU_TENSOR_MAP_L2_PROMOTION_NONE, CU_TENSOR_MAP_FLOAT_OOB_FILL_NONE);
            enc(&tmO, CU_TENSOR_MAP_DATA_TYPE_BFLOAT16, 5, d_out, gd, gs, box, es, CU_TENSOR_MAP_INTERLEAVE_NONE,
                CU_TENSOR_MAP_SWIZZLE_128B, CU_TENSOR_MAP_L2_PROMOTION_NONE, CU_TENSOR_MAP_FLOAT_OOB_FILL_NONE);
        }
        {
            cuuint64_t gd[4] = {64, 8, 3, (cuuint64_t)NHEADS * SK / 8};
            cuuint64_t gs[3] = {ROW_BYTES, 128, 8 * ROW_BYTES};
            enc(&tmK, CU_TENSOR_MAP_DATA_TYPE_BFLOAT16, 4, d_in[1], gd, gs, box, es, CU_TENSOR_MAP_INTERLEAVE_NONE,
                CU_TENSOR_MAP_SWIZZLE_128B, CU_TENSOR_MAP_L2_PROMOTION_NONE, CU_TENSOR_MAP_FLOAT_OOB_FILL_NONE);
            enc(&tmV, CU_TENSOR_MAP_DATA_TYPE_BFLOAT16, 4, d_in[2], gd, gs, box, es, CU_TENSOR_MAP_INTERLEAVE_NONE,
                CU_TENSOR_MAP_SWIZZLE_128B, CU_TENSOR_MAP_L2_PROMOTION_NONE, CU_TENSOR_MAP_FLOAT_OOB_FILL_NONE);
        }
        cudaFuncSetAttribute(attn_fwd_kernel, cudaFuncAttributeMaxDynamicSharedMemorySize, SMEM_BYTES);
        cached[0] = d_in[0]; cached[1] = d_in[1]; cached[2] = d_in[2]; cached[3] = d_out;
    }
    attn_fwd_kernel<<<2 * NUM_CLUSTERS, 384, SMEM_BYTES, cudaStreamPerThread>>>(tmQ, tmK, tmV, tmO, tmR, 0u, (const uint4*)d_in[0], (const uint4*)d_in[1],
                                                                                (const uint4*)d_in[2], (uint4*)d_out);
}
```

```cpp
#include <cuda_runtime.h>
#include <cuda_bf16.h>
#include <cuda.h>
#include <stdint.h>

namespace {

constexpr int NHEADS = 512;
constexpr int SQ = 848;
constexpr int SK = 512;
constexpr int DH = 192;
constexpr int ROW_BYTES = DH * 2;
constexpr int NBLK = SK / 64;
constexpr int NUM_CLUSTERS = 66;

constexpr uint32_t GRP_BYTES = 3072, SLAB_BYTES = 1024;
constexpr uint32_t BLK_BYTES = 64 * ROW_BYTES;
constexpr uint32_t REM_BYTES = 16 * ROW_BYTES;
constexpr uint32_t SM_BASE = 1024;
constexpr uint32_t SM_BAR = 0;
constexpr uint32_t SM_REM = 1024;
constexpr uint32_t SM_V = SM_REM + REM_BYTES;
constexpr uint32_t SM_K = SM_V + 3 * BLK_BYTES;
constexpr uint32_t SM_QO = SM_K + 4 * BLK_BYTES;
constexpr uint32_t SM_PT = SM_QO + 2 * BLK_BYTES;
constexpr uint32_t SMEM_BYTES = SM_PT + 2 * 2048;
#define T_KVPF 4
#define KROT 2
constexpr uint32_t BAR_FULL = SM_BAR;
constexpr uint32_t BAR_DONE = BAR_FULL + 32;
constexpr uint32_t BAR_QFULL = BAR_DONE + 32;
constexpr uint32_t BAR_OREADY = BAR_QFULL + 16;
constexpr uint32_t BAR_STORED = BAR_OREADY + 16;
constexpr uint32_t BAR_DUMMY = BAR_STORED + 16;
constexpr uint32_t BAR_REMFREE = BAR_DUMMY + 8;
constexpr uint32_t BAR_SUMS = BAR_REMFREE + 8;
constexpr uint32_t SM_REDO = BAR_SUMS + 8;
static_assert(SMEM_BYTES <= 232448, "smem");

constexpr int PRODUCER_REGS = 24, CONSUMER_REGS = 240;
#define STAGE_SPLIT 4
#define STG_CVTK 7
#define STG_POS 0xBA987654
#define STG_N1 4
#define P6N 24
#define MS0 1
#define SK0 0
#define SDK 2
#define PUB_B 1
constexpr float SCALE_LOG2E = 0.07216878364870323f * 1.4426950408889634f;
constexpr uint32_t SCALE_HI = 0x3DD53DD5u, SCALE_LO = 0x38EE38EEu;
constexpr uint32_t SUM_LOW = (127u - 14u) << 23, SUM_HIGH = (127u + 32u) << 23;

constexpr int EARLY_CLUSTERS = 10, START_STEP = 50;
constexpr int SCHED_COUNT = 29, SCHED_BREAKS = 30;
__constant__ __align__(8) uint16_t SCHED[NUM_CLUSTERS][36] = {
    {32768, 35, 206, 270, 298, 418, 466, 623, 4580, 428, 451, 11000, 8919, 9146, 8563, 7284, 3215, 1269, 1275, 19828, 9695, 1558, 1606, 1713, 1753, 1870, 1928, 2016, 0, 28, 4224, 36881, 17410, 4100, 0, 0},
    {32769, 11, 205, 268, 297, 417, 367, 2665, 747, 12717, 8871, 6849, 4817, 7097, 9072, 9331, 13422, 5447, 1352, 3442, 1475, 24084, 9799, 1689, 1785, 1850, 1964, 2010, 0, 28, 1088, 36930, 33026, 4112, 0, 1},
    {30722, 105, 182, 264, 299, 416, 468, 447, 2630, 4526, 962, 763, 10960, 9144, 2935, 13425, 15424, 9459, 32026, 9591, 3541, 5651, 24132, 9911, 1754, 1849, 1966, 2009, 0, 28, 16512, 37000, 2064, 4130, 0, 2},
    {30724, 3, 180, 269, 296, 463, 464, 616, 485, 779, 12737, 8903, 8914, 2883, 4468, 5183, 3213, 1268, 1310, 3451, 24022, 9767, 1605, 1716, 1786, 1868, 1929, 2017, 0, 28, 34848, 36896, 8706, 4104, 0, 3},
    {30725, 51, 192, 223, 6482, 730, 2513, 446, 581, 475, 11160, 9231, 7085, 13308, 7043, 5237, 5213, 9431, 3384, 3432, 5587, 22034, 9791, 1718, 1814, 1894, 1909, 1990, 0, 28, 2056, 36930, 16898, 4112, 0, 4},
    {32774, 19, 200, 245, 352, 521, 806, 439, 513, 534, 814, 875, 10926, 7005, 3173, 3127, 13377, 9475, 25876, 32150, 9655, 3612, 5715, 22161, 9967, 1834, 1942, 1970, 0, 28, 32896, 37136, 2050, 4162, 0, 5},
    {32776, 27, 154, 248, 287, 2840, 589, 403, 12868, 9039, 8758, 6635, 7172, 6999, 3105, 1187, 13458, 9415, 1328, 1382, 1508, 1528, 1609, 1728, 1800, 1836, 1954, 1982, 0, 28, 8720, 36866, 34946, 4096, 0, 6},
    {32777, 59, 152, 249, 335, 4889, 590, 2802, 917, 532, 563, 13114, 11213, 7133, 5047, 13461, 9347, 13550, 9519, 1418, 3555, 24060, 9807, 1726, 1764, 1840, 1896, 2036, 0, 28, 16400, 36932, 1026, 4113, 0, 7},
    {30730, 43, 193, 214, 343, 729, 651, 14781, 8895, 8670, 9118, 8571, 5038, 7159, 7140, 3195, 11341, 15582, 19770, 9631, 1470, 1585, 1597, 1742, 1809, 1885, 1905, 2024, 0, 28, 8464, 36872, 34882, 4096, 0, 8},
    {30732, 106, 147, 246, 311, 728, 469, 595, 14817, 12712, 9157, 13054, 7150, 4959, 13281, 9259, 7277, 9447, 1356, 1371, 24001, 9735, 1633, 1692, 1756, 1852, 1933, 2020, 0, 28, 8208, 36898, 32900, 4104, 0, 9},
    {22541, 100, 177, 10469, 10584, 8611, 408, 634, 546, 431, 960, 1054, 908, 869, 1109, 1208, 9417, 5374, 13685, 17861, 11797, 32337, 32434, 32538, 32578, 32682, 32716, 0, 0, 27, 512, 34816, 32, 2048, 0, 10},
    {18446, 109, 164, 4353, 8467, 689, 801, 638, 578, 543, 552, 1050, 680, 718, 3134, 1162, 3397, 17700, 5466, 13744, 32256, 32366, 32405, 32513, 32593, 32645, 32721, 0, 0, 27, 512, 34816, 16, 2048, 0, 11},
    {18448, 96, 187, 208, 302, 392, 412, 664, 629, 4989, 381, 938, 1013, 997, 1144, 3161, 1245, 3385, 5486, 5588, 5617, 7773, 9888, 10007, 32550, 32628, 32708, 0, 0, 27, 0, 34944, 4, 2048, 0, 12},
    {16401, 75, 201, 262, 354, 527, 805, 434, 512, 932, 553, 662, 1044, 714, 3152, 3228, 11590, 11554, 13698, 26036, 32293, 32340, 32442, 32489, 32552, 32656, 32761, 0, 0, 27, 32, 34816, 2, 2048, 0, 13},
    {18450, 67, 153, 250, 276, 389, 585, 820, 4737, 930, 6633, 661, 850, 984, 1185, 3201, 3306, 5431, 23905, 30181, 32250, 32374, 32426, 32522, 32545, 32672, 32704, 0, 0, 27, 0, 34818, 2, 2048, 0, 14},
    {16404, 118, 156, 4349, 6462, 2434, 4706, 4851, 6784, 4626, 809, 769, 7152, 985, 3254, 3202, 1284, 1326, 1368, 3562, 5678, 7805, 11949, 9941, 32610, 10095, 32754, 0, 0, 27, 0, 35328, 128, 2048, 0, 15},
    {14357, 83, 194, 212, 313, 396, 608, 4854, 625, 2936, 377, 770, 1007, 1017, 5245, 5208, 11484, 19720, 26008, 30141, 30260, 32346, 30412, 32497, 30558, 32633, 32745, 0, 0, 27, 4096, 34816, 2, 2048, 0, 16},
    {36886, 110, 2226, 224, 6492, 2738, 4688, 2717, 2596, 4770, 8901, 790, 834, 884, 1065, 1130, 3297, 17742, 30085, 32160, 9739, 7781, 18062, 32501, 32584, 10143, 32742, 0, 0, 27, 0, 35328, 0, 2064, 0, 17},
    {38936, 102, 179, 228, 349, 422, 409, 668, 544, 2726, 738, 3100, 909, 868, 5178, 3214, 1348, 1309, 1398, 3532, 3598, 13956, 32393, 32542, 32581, 32732, 10191, 0, 0, 27, 0, 35840, 4, 2048, 0, 18},
    {14361, 125, 165, 2306, 10512, 4788, 8593, 2684, 6790, 6744, 2752, 2774, 956, 2418, 5174, 3142, 19718, 19728, 21909, 32170, 32285, 9835, 13970, 32510, 32660, 10119, 32725, 0, 0, 27, 0, 35328, 0, 2080, 0, 19},
    {12314, 98, 198, 12497, 10552, 6538, 4510, 4762, 2522, 2650, 7176, 936, 3062, 4998, 3184, 11356, 13525, 25881, 32105, 32201, 32313, 32370, 9891, 32502, 32548, 32728, 10183, 0, 0, 27, 0, 35840, 0, 2112, 0, 20},
    {36892, 124, 203, 260, 359, 522, 499, 432, 514, 933, 813, 876, 1045, 713, 1105, 1181, 1252, 1360, 1408, 1462, 1572, 1621, 1666, 1768, 1798, 1941, 2042, 0, 0, 27, 16, 2048, 68, 34816, 0, 21},
    {6173, 114, 155, 252, 317, 388, 591, 753, 916, 928, 488, 1024, 1040, 1058, 1184, 5267, 1220, 1330, 1376, 1466, 1577, 1608, 1729, 1806, 1826, 1918, 1980, 0, 0, 27, 64, 2048, 32772, 34816, 0, 22},
    {8222, 117, 137, 8443, 316, 799, 588, 752, 918, 533, 812, 827, 974, 988, 1190, 1178, 1218, 1361, 1433, 1506, 1533, 1614, 1725, 1762, 1842, 1898, 1969, 0, 0, 27, 32, 2048, 2056, 34816, 0, 23},
    {6176, 113, 2188, 4307, 314, 397, 612, 698, 628, 2943, 376, 774, 1002, 1019, 1150, 1100, 1242, 1341, 1436, 1490, 1584, 1624, 1738, 1813, 1882, 1950, 2028, 0, 0, 27, 512, 2048, 8200, 34816, 0, 24},
    {40993, 107, 176, 247, 300, 731, 470, 444, 486, 426, 966, 764, 905, 864, 1084, 1212, 1254, 1340, 1373, 1472, 1540, 1632, 1694, 1758, 1853, 1932, 2021, 0, 0, 27, 8, 2048, 34, 34816, 0, 25},
    {4130, 99, 181, 230, 345, 421, 2458, 12958, 4646, 6821, 3015, 1053, 910, 4966, 9273, 7355, 1226, 1277, 1374, 1478, 1569, 1618, 7832, 1752, 1857, 1930, 1993, 0, 0, 27, 1024, 2048, 32770, 34816, 0, 26},
    {18468, 2168, 4257, 8451, 273, 4790, 2848, 633, 583, 542, 737, 1048, 681, 715, 1120, 1161, 1344, 1313, 1405, 1457, 1542, 1645, 3768, 14072, 3926, 1920, 2000, 0, 0, 27, 256, 2048, 8200, 34816, 0, 27},
    {55333, 10330, 195, 210, 6445, 12681, 6557, 2713, 4726, 2940, 2428, 2985, 1012, 2949, 1142, 1118, 1236, 3391, 15724, 9659, 1552, 3650, 7861, 16137, 20325, 1910, 1989, 0, 0, 27, 0, 2050, 4, 34824, 0, 28},
    {53286, 123, 202, 266, 2401, 4616, 807, 433, 515, 2982, 554, 877, 1046, 712, 1106, 1182, 1253, 1312, 1409, 3509, 3622, 7766, 22201, 3818, 12073, 12177, 1968, 0, 0, 27, 64, 2048, 258, 34816, 0, 29},
    {36904, 115, 157, 239, 277, 794, 584, 822, 642, 929, 493, 1026, 1042, 1059, 1122, 1168, 3270, 3377, 1381, 1464, 11769, 5748, 11973, 28429, 26400, 8061, 10173, 0, 0, 27, 8, 2048, 8194, 34816, 0, 30},
    {30761, 4217, 8328, 6478, 2342, 2435, 10849, 8948, 7056, 6673, 4911, 660, 971, 990, 1189, 1176, 1217, 3382, 3482, 5601, 9768, 9804, 14012, 28389, 28470, 1897, 2038, 0, 0, 27, 1024, 2048, 4128, 34816, 0, 31},
    {47146, 10329, 4238, 8534, 4421, 4491, 10854, 8888, 6775, 894, 378, 773, 3057, 5094, 7290, 9306, 9435, 3337, 5534, 9660, 3637, 15934, 24269, 26386, 28508, 28528, 24554, 0, 0, 27, 256, 2048, 32, 34817, 0, 32},
    {45100, 2152, 8360, 6409, 2394, 2697, 593, 667, 6693, 8865, 8902, 4884, 4928, 4469, 5162, 3176, 3296, 9546, 7558, 7589, 11786, 9831, 13964, 9947, 20280, 30618, 32766, 0, 0, 27, 0, 2080, 128, 34944, 0, 33},
    {43053, 8293, 8365, 4323, 8542, 10660, 6559, 632, 545, 676, 961, 1051, 904, 866, 1110, 1210, 1224, 3324, 1372, 11716, 26146, 30273, 26266, 26393, 26432, 24489, 32718, 0, 0, 27, 64, 2048, 2056, 34816, 0, 34},
    {45102, 10369, 2211, 261, 10518, 8887, 804, 637, 576, 540, 736, 1049, 683, 717, 1085, 1160, 3394, 13606, 9598, 7602, 28161, 20076, 32406, 28416, 30549, 32642, 32724, 0, 0, 27, 32, 2048, 4100, 34816, 0, 35},
    {41008, 6278, 8413, 4376, 4386, 574, 400, 816, 845, 606, 1033, 659, 2897, 4994, 1202, 1156, 7376, 3368, 7570, 7598, 24052, 30321, 32420, 32465, 10087, 32676, 10171, 0, 0, 27, 0, 2304, 2048, 35840, 0, 36},
    {41009, 6238, 139, 254, 6436, 8582, 8778, 6965, 5009, 6749, 4906, 3077, 4948, 2997, 3252, 3241, 3309, 5390, 11661, 15853, 22006, 30328, 32430, 9943, 32565, 10107, 32694, 0, 0, 27, 0, 2176, 4, 35328, 0, 37},
    {20530, 10332, 6302, 4428, 4418, 569, 510, 982, 842, 560, 830, 1030, 958, 950, 11337, 19626, 9451, 9485, 11657, 26089, 32300, 32380, 9903, 20182, 10035, 32620, 32752, 0, 0, 27, 0, 2112, 0, 35073, 0, 38},
    {38964, 4187, 196, 6357, 8511, 398, 613, 4853, 2674, 890, 2971, 772, 1000, 1016, 1148, 1102, 3288, 13578, 21849, 21969, 13878, 32345, 32456, 32528, 32600, 32632, 32750, 0, 0, 27, 16, 2048, 1026, 34816, 0, 39},
    {26677, 6252, 14506, 6448, 2781, 648, 594, 748, 777, 672, 708, 789, 856, 4981, 17452, 9323, 1250, 17737, 13700, 21924, 32265, 32384, 32492, 32516, 10063, 32664, 10235, 0, 0, 27, 0, 2304, 32768, 35840, 0, 40},
    {30774, 24673, 6318, 4321, 2506, 2408, 598, 746, 780, 450, 740, 784, 838, 7026, 17453, 17516, 19697, 9499, 23920, 30158, 32268, 32389, 9871, 20252, 32582, 10155, 32712, 0, 0, 27, 0, 2112, 0, 35330, 0, 41},
    {38968, 14466, 6310, 2304, 2504, 502, 2450, 4846, 644, 601, 706, 724, 9149, 14705, 13365, 15428, 15618, 17682, 19933, 9643, 32286, 32360, 32493, 9991, 32592, 32646, 10195, 0, 0, 27, 0, 2176, 0, 35848, 0, 42},
    {38969, 16517, 4318, 12570, 18721, 8765, 2453, 818, 9036, 603, 5130, 657, 848, 2945, 1201, 1158, 13522, 23849, 28049, 32173, 32245, 9847, 5797, 32464, 10019, 32678, 32697, 0, 0, 27, 0, 2080, 512, 35072, 0, 43},
    {55354, 12381, 16522, 8521, 2341, 2433, 6649, 11220, 2894, 562, 828, 969, 3108, 11184, 7347, 7296, 7429, 7469, 32136, 32238, 9719, 9850, 7852, 32466, 32608, 32634, 10163, 0, 0, 27, 0, 2064, 16384, 35840, 0, 44},
    {55356, 18548, 18573, 2381, 4416, 14904, 12796, 7120, 9032, 4657, 2873, 3016, 9253, 15282, 13460, 13485, 13653, 15638, 9611, 32232, 9775, 7801, 22184, 32468, 32609, 32733, 10227, 0, 0, 27, 0, 2064, 0, 35844, 0, 45},
    {22589, 26712, 12485, 14677, 14660, 10892, 8813, 10941, 4569, 9116, 7182, 7084, 9213, 9186, 13386, 15532, 15702, 15628, 9579, 32162, 32312, 9823, 32418, 32498, 32585, 32734, 10219, 0, 0, 27, 0, 2080, 0, 35844, 0, 46},
    {38974, 22676, 8363, 10466, 2399, 688, 2515, 618, 487, 425, 964, 765, 906, 865, 1108, 1214, 1229, 1272, 1401, 1474, 1541, 1634, 1693, 1774, 1797, 1934, 2045, 0, 0, 27, 272, 34816, 68, 2048, 0, 47},
    {55360, 20629, 16556, 16692, 14793, 14697, 10682, 10989, 11021, 4548, 2787, 725, 7055, 374, 1107, 9401, 9423, 1274, 1400, 1496, 1568, 1600, 1712, 1816, 1869, 1965, 1994, 0, 0, 27, 4096, 34817, 17408, 2048, 0, 48},
    {55361, 8323, 160, 271, 274, 693, 802, 2683, 577, 541, 559, 878, 682, 716, 1121, 1074, 1345, 1317, 1404, 1497, 1538, 1616, 1684, 1794, 1876, 1921, 2018, 0, 0, 27, 1032, 34816, 130, 2048, 0, 49},
    {55362, 20612, 18652, 14617, 12576, 12860, 12692, 9011, 6789, 2983, 494, 2706, 1043, 1056, 1127, 1169, 1221, 1333, 1378, 1465, 1553, 1653, 1730, 1804, 1892, 1953, 1978, 0, 0, 27, 16896, 34816, 4224, 2048, 0, 50},
    {55364, 26736, 20716, 16668, 8483, 8576, 4600, 3026, 2962, 6679, 4904, 5121, 854, 3034, 3234, 3227, 17641, 19764, 9575, 1510, 1534, 1610, 1734, 1766, 1838, 1916, 1972, 0, 0, 27, 512, 34820, 32784, 2048, 0, 51},
    {55365, 30842, 30957, 22858, 12609, 10737, 8699, 3025, 5015, 528, 2538, 2816, 3058, 5083, 3236, 13465, 11456, 9559, 1380, 1504, 1578, 1613, 1732, 1761, 1841, 1901, 2033, 0, 0, 27, 256, 34818, 8256, 2048, 0, 52},
    {55366, 30904, 24792, 24916, 8515, 2698, 6759, 8889, 624, 889, 8574, 771, 1001, 3066, 7289, 3151, 1241, 1342, 1437, 1488, 1586, 1596, 1737, 20244, 8025, 1906, 2029, 0, 0, 27, 32832, 34816, 2064, 2048, 0, 53},
    {55368, 30866, 20649, 16690, 13022, 18798, 10836, 6626, 11016, 6597, 2810, 8979, 857, 2934, 5160, 13417, 19698, 32077, 9607, 1446, 1587, 20070, 9887, 7901, 18238, 18332, 2044, 0, 0, 27, 0, 34884, 2048, 2064, 0, 54},
    {55369, 30864, 30961, 28982, 14798, 8554, 8632, 6889, 8739, 454, 741, 2834, 833, 7015, 1080, 1164, 1270, 3356, 1393, 1485, 1549, 18054, 32394, 32541, 10051, 32680, 10207, 0, 0, 27, 8192, 35840, 256, 2304, 0, 55},
    {55370, 30846, 30882, 31076, 29197, 12789, 18869, 10758, 4632, 6700, 4970, 6829, 9147, 2416, 7220, 19525, 21761, 9511, 1428, 1452, 1562, 13929, 32400, 9979, 22354, 10135, 2002, 0, 0, 27, 0, 35330, 4096, 2176, 0, 56},
    {55372, 30908, 30958, 31005, 23325, 8763, 406, 817, 4743, 10844, 8684, 4752, 1041, 2944, 1200, 1157, 1233, 5418, 3472, 3530, 7664, 26224, 32422, 9995, 26405, 10151, 1976, 0, 0, 27, 256, 35328, 32, 2176, 0, 57},
    {55373, 30909, 30952, 31006, 17182, 19002, 14842, 7123, 472, 565, 829, 3079, 853, 7092, 5301, 9384, 3304, 7468, 7564, 1516, 1531, 13950, 9927, 22240, 20269, 18341, 16309, 0, 0, 27, 2048, 34880, 128, 2064, 0, 58},
    {55374, 30910, 30953, 31048, 31516, 18930, 8701, 5077, 6985, 6708, 13112, 7114, 9254, 5041, 7318, 9387, 23788, 27925, 30094, 9711, 7725, 7803, 13993, 9959, 28468, 22382, 2037, 0, 0, 27, 0, 34952, 32768, 2080, 0, 59},
    {55376, 30905, 30937, 31057, 22854, 27278, 21102, 12988, 12764, 9117, 9229, 7148, 5118, 9187, 5192, 19630, 25940, 9487, 7533, 26017, 13810, 26204, 9931, 12016, 10079, 26525, 32706, 0, 0, 27, 0, 35074, 8192, 2112, 0, 60},
    {55377, 30870, 30962, 31025, 31452, 24941, 27221, 10720, 13066, 13209, 8953, 11245, 9050, 7136, 11310, 7372, 3312, 5451, 28126, 9639, 30216, 28260, 32397, 32500, 10043, 32665, 10215, 0, 0, 27, 0, 35848, 0, 2306, 0, 61},
    {55378, 30865, 30960, 31029, 31181, 20844, 16825, 13032, 8974, 22976, 2790, 11025, 4933, 9073, 5309, 3278, 3321, 1402, 1498, 1483, 26136, 9863, 32392, 10011, 28484, 10127, 32717, 0, 0, 27, 0, 35360, 0, 2184, 0, 62},
    {55380, 30848, 30954, 31077, 25100, 27124, 22964, 20997, 14874, 6701, 17257, 12972, 11102, 5222, 7217, 9283, 23808, 23825, 9623, 11689, 26137, 32362, 9875, 9981, 10071, 32644, 32726, 0, 0, 27, 0, 35076, 32768, 2112, 0, 63},
    {55381, 30906, 30938, 31056, 31180, 25229, 21100, 15038, 18909, 13210, 9228, 9131, 836, 4996, 7282, 9311, 1238, 5400, 21866, 13768, 28218, 26206, 32417, 9971, 32586, 10103, 32705, 0, 0, 27, 32768, 35328, 2048, 2176, 0, 64},
    {55382, 30924, 30964, 31078, 27150, 27120, 18870, 20996, 21017, 14894, 13160, 9164, 9052, 7268, 9264, 7234, 3410, 3347, 21980, 23976, 9759, 32385, 9915, 16124, 10031, 32658, 32760, 0, 0, 27, 0, 35088, 0, 2114, 0, 65},
};

__device__ __forceinline__ uint32_t smem_u32(const void* p) { return (uint32_t)__cvta_generic_to_shared(p); }
__device__ __forceinline__ void mbar_init(uint32_t bar, uint32_t cnt) {
    asm volatile("mbarrier.init.shared::cta.b64 [%0], %1;" ::"r"(bar), "r"(cnt));
}
__device__ __forceinline__ void mbar_expect_tx(uint32_t bar, uint32_t bytes) {
    asm volatile("mbarrier.arrive.expect_tx.shared::cta.b64 _, [%0], %1;" ::"r"(bar), "r"(bytes) : "memory");
}
__device__ __forceinline__ void mbar_arrive(uint32_t bar) {
    asm volatile("mbarrier.arrive.shared::cta.b64 _, [%0];" ::"r"(bar) : "memory");
}
__device__ __forceinline__ void mbar_arrive_cluster_pred(uint32_t addr, uint32_t pred) {
    asm volatile(
        "{\n.reg .pred p;\n"
        "setp.ne.u32 p, %1, 0;\n"
        "@p mbarrier.arrive.shared::cluster.b64 _, [%0];\n}\n" ::"r"(addr), "r"(pred) : "memory");
}
__device__ __forceinline__ void mbar_arrive_pred(uint32_t addr, uint32_t pred) {
    asm volatile(
        "{\n.reg .pred p;\n"
        "setp.ne.u32 p, %1, 0;\n"
        "@p mbarrier.arrive.shared::cta.b64 _, [%0];\n}\n" ::"r"(addr), "r"(pred) : "memory");
}
__device__ __forceinline__ uint32_t mapa(uint32_t addr, uint32_t cta) {
    uint32_t r;
    asm("mapa.shared::cluster.u32 %0, %1, %2;" : "=r"(r) : "r"(addr), "r"(cta));
    return r;
}
__device__ __forceinline__ void mbar_wait(uint32_t bar, uint32_t parity) {
    asm volatile(
        "{\n.reg .pred p;\n"
        "WAIT_LOOP:\n"
        "mbarrier.try_wait.parity.shared::cta.b64 p, [%0], %1;\n"
        "@p bra WAIT_DONE;\n"
        "bra WAIT_LOOP;\n"
        "WAIT_DONE:\n}\n" ::"r"(bar), "r"(parity) : "memory");
}
__device__ __forceinline__ void mbar_sleep(uint32_t bar, uint32_t parity) {
    asm volatile(
        "{\n.reg .pred p;\n"
        "WAIT_LOOP:\n"
        "mbarrier.try_wait.parity.shared::cta.b64 p, [%0], %1, 0x989680;\n"
        "@p bra WAIT_DONE;\n"
        "bra WAIT_LOOP;\n"
        "WAIT_DONE:\n}\n" ::"r"(bar), "r"(parity) : "memory");
}
__device__ __forceinline__ bool elect_one() {
    uint32_t pred;
    asm volatile("{\n.reg .pred p;\nelect.sync _|p, 0xffffffff;\nselp.u32 %0, 1, 0, p;\n}\n" : "=r"(pred));
    return pred != 0;
}
__device__ __forceinline__ void tma_load_kv(uint32_t dst, const CUtensorMap* tm, int g, uint32_t bar) {
    asm volatile(
        "cp.async.bulk.tensor.4d.shared::cluster.global.mbarrier::complete_tx::bytes [%0], [%1, {%3, %3, %3, %4}], [%2];" ::"r"(dst),
        "l"(tm), "r"(bar), "r"(0), "r"(g)
        : "memory");
}
__device__ __forceinline__ void tma_load_kv_mc(uint32_t dst, const CUtensorMap* tm, int g, uint32_t bar) {
    asm volatile(
        "cp.async.bulk.tensor.4d.shared::cluster.global.mbarrier::complete_tx::bytes.multicast::cluster [%0], [%1, {%3, %3, %3, %4}], [%2], %5;" ::"r"(dst),
        "l"(tm), "r"(bar), "r"(0), "r"(g), "h"((uint16_t)3)
        : "memory");
}
__device__ __forceinline__ void tma_load_q(uint32_t dst, const CUtensorMap* tm, int g, int head, uint32_t bar) {
    asm volatile(
        "cp.async.bulk.tensor.5d.shared::cluster.global.mbarrier::complete_tx::bytes [%0], [%1, {%3, %3, %3, %4, %5}], [%2];" ::"r"(dst),
        "l"(tm), "r"(bar), "r"(0), "r"(g), "r"(head)
        : "memory");
}
__device__ __forceinline__ void tma_store_o(const CUtensorMap* tm, uint32_t src, int g, int head) {
    asm volatile("cp.async.bulk.tensor.5d.global.shared::cta.bulk_group [%0, {%2, %2, %2, %3, %4}], [%1];" ::"l"(tm),
                 "r"(src), "r"(0), "r"(g), "r"(head)
                 : "memory");
}
__device__ __forceinline__ void bulk_commit() { asm volatile("cp.async.bulk.commit_group;" ::: "memory"); }
__device__ __forceinline__ void bulk_wait_read() { asm volatile("cp.async.bulk.wait_group.read 0;" ::: "memory"); }
__device__ __forceinline__ void fence_async_smem() { asm volatile("fence.proxy.async.shared::cta;" ::: "memory"); }
__device__ __forceinline__ void stsm_x4(uint32_t addr, uint32_t r0, uint32_t r1, uint32_t r2, uint32_t r3) {
    asm volatile("stmatrix.sync.aligned.m8n8.x4.shared.b16 [%0], {%1, %2, %3, %4};" ::"r"(addr), "r"(r0), "r"(r1), "r"(r2), "r"(r3) : "memory");
}
__device__ __forceinline__ void ldsm_x4(uint32_t addr, uint32_t& r0, uint32_t& r1, uint32_t& r2, uint32_t& r3) {
    asm volatile("ldmatrix.sync.aligned.m8n8.x4.shared.b16 {%0, %1, %2, %3}, [%4];" : "=r"(r0), "=r"(r1), "=r"(r2), "=r"(r3) : "r"(addr) : "memory");
}
__device__ __forceinline__ void wgmma_fence() { asm volatile("wgmma.fence.sync.aligned;" ::: "memory"); }
__device__ __forceinline__ void wgmma_commit() { asm volatile("wgmma.commit_group.sync.aligned;" ::: "memory"); }
template <int N>
__device__ __forceinline__ void wgmma_wait() { asm volatile("wgmma.wait_group.sync.aligned %0;" ::"n"(N) : "memory"); }
__device__ __forceinline__ void bar_sync(int id, int n) { asm volatile("bar.sync %0, %1;" ::"r"(id), "r"(n) : "memory"); }
__device__ __forceinline__ void bar_arrive(int id, int n) { asm volatile("bar.arrive %0, %1;" ::"r"(id), "r"(n) : "memory"); }
__device__ __forceinline__ float ex2(float x) {
    float y;
    asm("ex2.approx.ftz.f32 %0, %1;" : "=f"(y) : "f"(x));
    return y;
}
__device__ __forceinline__ uint32_t pack_bf16(float lo, float hi) {
    uint32_t r;
    asm("cvt.rn.bf16x2.f32 %0, %1, %2;" : "=r"(r) : "f"(hi), "f"(lo));
    return r;
}
template <int N>
__device__ __forceinline__ void fence_regs(float (&r)[N]) {
#pragma unroll
    for (int i = 0; i < N; i++) asm volatile("" : "+f"(r[i])::"memory");
}
template <int N>
__device__ __forceinline__ void fence_regs(uint32_t (&r)[N]) {
#pragma unroll
    for (int i = 0; i < N; i++) asm volatile("" : "+r"(r[i])::"memory");
}
template <int N>
__device__ __forceinline__ void forget(float (&r)[N]) {
#pragma unroll
    for (int i = 0; i < N; i++) r[i] = 0.f;
}
__device__ __forceinline__ uint64_t make_desc(uint32_t lo, uint32_t hi) { return ((uint64_t)hi << 32) | lo; }
constexpr uint32_t DESC_HI = (GRP_BYTES >> 4) | (1u << 30);

__device__ __forceinline__ void wgmma_qk(float (&d)[32], uint32_t a0, uint32_t a1, uint32_t a2, uint32_t a3, uint64_t descB) {
    asm volatile(
        "{\n.reg .pred p;\n"
        "setp.eq.b32 p, 0, 0;\n"
        "wgmma.mma_async.sync.aligned.m64n64k16.f32.bf16.bf16 "
        "{%0, %1, %2, %3, %4, %5, %6, %7, %8, %9, %10, %11, %12, %13, %14, %15, "
        "%16, %17, %18, %19, %20, %21, %22, %23, %24, %25, %26, %27, %28, %29, %30, %31}, "
        "{%32, %33, %34, %35}, %36, p, 1, 1, 0;\n}\n"
        : "+f"(d[0]), "+f"(d[1]), "+f"(d[2]), "+f"(d[3]), "+f"(d[4]), "+f"(d[5]), "+f"(d[6]), "+f"(d[7]),
          "+f"(d[8]), "+f"(d[9]), "+f"(d[10]), "+f"(d[11]), "+f"(d[12]), "+f"(d[13]), "+f"(d[14]), "+f"(d[15]),
          "+f"(d[16]), "+f"(d[17]), "+f"(d[18]), "+f"(d[19]), "+f"(d[20]), "+f"(d[21]), "+f"(d[22]), "+f"(d[23]),
          "+f"(d[24]), "+f"(d[25]), "+f"(d[26]), "+f"(d[27]), "+f"(d[28]), "+f"(d[29]), "+f"(d[30]), "+f"(d[31])
        : "r"(a0), "r"(a1), "r"(a2), "r"(a3), "l"(descB));
}

__device__ __forceinline__ void wgmma_qk_init(float (&d)[32], uint32_t a0, uint32_t a1, uint32_t a2, uint32_t a3, uint64_t descB) {
    asm volatile(
        "{\n.reg .pred p;\n"
        "setp.ne.b32 p, 0, 0;\n"
        "wgmma.mma_async.sync.aligned.m64n64k16.f32.bf16.bf16 "
        "{%0, %1, %2, %3, %4, %5, %6, %7, %8, %9, %10, %11, %12, %13, %14, %15, "
        "%16, %17, %18, %19, %20, %21, %22, %23, %24, %25, %26, %27, %28, %29, %30, %31}, "
        "{%32, %33, %34, %35}, %36, p, 1, 1, 0;\n}\n"
        : "=f"(d[0]), "=f"(d[1]), "=f"(d[2]), "=f"(d[3]), "=f"(d[4]), "=f"(d[5]), "=f"(d[6]), "=f"(d[7]),
          "=f"(d[8]), "=f"(d[9]), "=f"(d[10]), "=f"(d[11]), "=f"(d[12]), "=f"(d[13]), "=f"(d[14]), "=f"(d[15]),
          "=f"(d[16]), "=f"(d[17]), "=f"(d[18]), "=f"(d[19]), "=f"(d[20]), "=f"(d[21]), "=f"(d[22]), "=f"(d[23]),
          "=f"(d[24]), "=f"(d[25]), "=f"(d[26]), "=f"(d[27]), "=f"(d[28]), "=f"(d[29]), "=f"(d[30]), "=f"(d[31])
        : "r"(a0), "r"(a1), "r"(a2), "r"(a3), "l"(descB));
}

__device__ __forceinline__ void wgmma_pv(float (&d)[96], uint32_t a0, uint32_t a1, uint32_t a2, uint32_t a3, uint64_t descB) {
    asm volatile(
        "{\n.reg .pred p;\n"
        "setp.eq.b32 p, 0, 0;\n"
        "wgmma.mma_async.sync.aligned.m64n192k16.f32.bf16.bf16 "
        "{%0, %1, %2, %3, %4, %5, %6, %7, %8, %9, %10, %11, %12, %13, %14, %15, "
        "%16, %17, %18, %19, %20, %21, %22, %23, %24, %25, %26, %27, %28, %29, %30, %31, "
        "%32, %33, %34, %35, %36, %37, %38, %39, %40, %41, %42, %43, %44, %45, %46, %47, "
        "%48, %49, %50, %51, %52, %53, %54, %55, %56, %57, %58, %59, %60, %61, %62, %63, "
        "%64, %65, %66, %67, %68, %69, %70, %71, %72, %73, %74, %75, %76, %77, %78, %79, "
        "%80, %81, %82, %83, %84, %85, %86, %87, %88, %89, %90, %91, %92, %93, %94, %95}, "
        "{%96, %97, %98, %99}, %100, p, 1, 1, 1;\n}\n"
        : "+f"(d[0]), "+f"(d[1]), "+f"(d[2]), "+f"(d[3]), "+f"(d[4]), "+f"(d[5]), "+f"(d[6]), "+f"(d[7]),
          "+f"(d[8]), "+f"(d[9]), "+f"(d[10]), "+f"(d[11]), "+f"(d[12]), "+f"(d[13]), "+f"(d[14]), "+f"(d[15]),
          "+f"(d[16]), "+f"(d[17]), "+f"(d[18]), "+f"(d[19]), "+f"(d[20]), "+f"(d[21]), "+f"(d[22]), "+f"(d[23]),
          "+f"(d[24]), "+f"(d[25]), "+f"(d[26]), "+f"(d[27]), "+f"(d[28]), "+f"(d[29]), "+f"(d[30]), "+f"(d[31]),
          "+f"(d[32]), "+f"(d[33]), "+f"(d[34]), "+f"(d[35]), "+f"(d[36]), "+f"(d[37]), "+f"(d[38]), "+f"(d[39]),
          "+f"(d[40]), "+f"(d[41]), "+f"(d[42]), "+f"(d[43]), "+f"(d[44]), "+f"(d[45]), "+f"(d[46]), "+f"(d[47]),
          "+f"(d[48]), "+f"(d[49]), "+f"(d[50]), "+f"(d[51]), "+f"(d[52]), "+f"(d[53]), "+f"(d[54]), "+f"(d[55]),
          "+f"(d[56]), "+f"(d[57]), "+f"(d[58]), "+f"(d[59]), "+f"(d[60]), "+f"(d[61]), "+f"(d[62]), "+f"(d[63]),
          "+f"(d[64]), "+f"(d[65]), "+f"(d[66]), "+f"(d[67]), "+f"(d[68]), "+f"(d[69]), "+f"(d[70]), "+f"(d[71]),
          "+f"(d[72]), "+f"(d[73]), "+f"(d[74]), "+f"(d[75]), "+f"(d[76]), "+f"(d[77]), "+f"(d[78]), "+f"(d[79]),
          "+f"(d[80]), "+f"(d[81]), "+f"(d[82]), "+f"(d[83]), "+f"(d[84]), "+f"(d[85]), "+f"(d[86]), "+f"(d[87]),
          "+f"(d[88]), "+f"(d[89]), "+f"(d[90]), "+f"(d[91]), "+f"(d[92]), "+f"(d[93]), "+f"(d[94]), "+f"(d[95])
        : "r"(a0), "r"(a1), "r"(a2), "r"(a3), "l"(descB));
}

__device__ __forceinline__ void wgmma_pv_init(float (&d)[96], uint32_t a0, uint32_t a1, uint32_t a2, uint32_t a3, uint64_t descB) {
    asm volatile(
        "{\n.reg .pred p;\n"
        "setp.ne.b32 p, 0, 0;\n"
        "wgmma.mma_async.sync.aligned.m64n192k16.f32.bf16.bf16 "
        "{%0, %1, %2, %3, %4, %5, %6, %7, %8, %9, %10, %11, %12, %13, %14, %15, "
        "%16, %17, %18, %19, %20, %21, %22, %23, %24, %25, %26, %27, %28, %29, %30, %31, "
        "%32, %33, %34, %35, %36, %37, %38, %39, %40, %41, %42, %43, %44, %45, %46, %47, "
        "%48, %49, %50, %51, %52, %53, %54, %55, %56, %57, %58, %59, %60, %61, %62, %63, "
        "%64, %65, %66, %67, %68, %69, %70, %71, %72, %73, %74, %75, %76, %77, %78, %79, "
        "%80, %81, %82, %83, %84, %85, %86, %87, %88, %89, %90, %91, %92, %93, %94, %95}, "
        "{%96, %97, %98, %99}, %100, p, 1, 1, 1;\n}\n"
        : "=f"(d[0]), "=f"(d[1]), "=f"(d[2]), "=f"(d[3]), "=f"(d[4]), "=f"(d[5]), "=f"(d[6]), "=f"(d[7]),
          "=f"(d[8]), "=f"(d[9]), "=f"(d[10]), "=f"(d[11]), "=f"(d[12]), "=f"(d[13]), "=f"(d[14]), "=f"(d[15]),
          "=f"(d[16]), "=f"(d[17]), "=f"(d[18]), "=f"(d[19]), "=f"(d[20]), "=f"(d[21]), "=f"(d[22]), "=f"(d[23]),
          "=f"(d[24]), "=f"(d[25]), "=f"(d[26]), "=f"(d[27]), "=f"(d[28]), "=f"(d[29]), "=f"(d[30]), "=f"(d[31]),
          "=f"(d[32]), "=f"(d[33]), "=f"(d[34]), "=f"(d[35]), "=f"(d[36]), "=f"(d[37]), "=f"(d[38]), "=f"(d[39]),
          "=f"(d[40]), "=f"(d[41]), "=f"(d[42]), "=f"(d[43]), "=f"(d[44]), "=f"(d[45]), "=f"(d[46]), "=f"(d[47]),
          "=f"(d[48]), "=f"(d[49]), "=f"(d[50]), "=f"(d[51]), "=f"(d[52]), "=f"(d[53]), "=f"(d[54]), "=f"(d[55]),
          "=f"(d[56]), "=f"(d[57]), "=f"(d[58]), "=f"(d[59]), "=f"(d[60]), "=f"(d[61]), "=f"(d[62]), "=f"(d[63]),
          "=f"(d[64]), "=f"(d[65]), "=f"(d[66]), "=f"(d[67]), "=f"(d[68]), "=f"(d[69]), "=f"(d[70]), "=f"(d[71]),
          "=f"(d[72]), "=f"(d[73]), "=f"(d[74]), "=f"(d[75]), "=f"(d[76]), "=f"(d[77]), "=f"(d[78]), "=f"(d[79]),
          "=f"(d[80]), "=f"(d[81]), "=f"(d[82]), "=f"(d[83]), "=f"(d[84]), "=f"(d[85]), "=f"(d[86]), "=f"(d[87]),
          "=f"(d[88]), "=f"(d[89]), "=f"(d[90]), "=f"(d[91]), "=f"(d[92]), "=f"(d[93]), "=f"(d[94]), "=f"(d[95])
        : "r"(a0), "r"(a1), "r"(a2), "r"(a3), "l"(descB));
}

__device__ __forceinline__ void wgmma_rk(float (&d)[8], uint64_t descA, uint64_t descB) {
    asm volatile(
        "{\n.reg .pred p;\n"
        "setp.eq.b32 p, 0, 0;\n"
        "wgmma.mma_async.sync.aligned.m64n16k16.f32.bf16.bf16 "
        "{%0, %1, %2, %3, %4, %5, %6, %7}, "
        "%8, %9, p, 1, 1, 0, 0;\n}\n"
        : "+f"(d[0]), "+f"(d[1]), "+f"(d[2]), "+f"(d[3]), "+f"(d[4]), "+f"(d[5]), "+f"(d[6]), "+f"(d[7])
        : "l"(descA), "l"(descB));
}

__device__ __forceinline__ void wgmma_rk_init(float (&d)[8], uint64_t descA, uint64_t descB) {
    asm volatile(
        "{\n.reg .pred p;\n"
        "setp.ne.b32 p, 0, 0;\n"
        "wgmma.mma_async.sync.aligned.m64n16k16.f32.bf16.bf16 "
        "{%0, %1, %2, %3, %4, %5, %6, %7}, "
        "%8, %9, p, 1, 1, 0, 0;\n}\n"
        : "=f"(d[0]), "=f"(d[1]), "=f"(d[2]), "=f"(d[3]), "=f"(d[4]), "=f"(d[5]), "=f"(d[6]), "=f"(d[7])
        : "l"(descA), "l"(descB));
}

__device__ __forceinline__ void wgmma_rv(float (&d)[8], uint64_t descA, uint64_t descB) {
    asm volatile(
        "{\n.reg .pred p;\n"
        "setp.eq.b32 p, 0, 0;\n"
        "wgmma.mma_async.sync.aligned.m64n16k16.f32.bf16.bf16 "
        "{%0, %1, %2, %3, %4, %5, %6, %7}, "
        "%8, %9, p, 1, 1, 1, 0;\n}\n"
        : "+f"(d[0]), "+f"(d[1]), "+f"(d[2]), "+f"(d[3]), "+f"(d[4]), "+f"(d[5]), "+f"(d[6]), "+f"(d[7])
        : "l"(descA), "l"(descB));
}

__device__ __forceinline__ void wgmma_rl(float (&d)[8], uint32_t a0, uint32_t a1, uint32_t a2, uint32_t a3, uint64_t descB) {
    asm volatile(
        "{\n.reg .pred p;\n"
        "setp.eq.b32 p, 0, 0;\n"
        "wgmma.mma_async.sync.aligned.m64n16k16.f32.bf16.bf16 "
        "{%0, %1, %2, %3, %4, %5, %6, %7}, "
        "{%8, %9, %10, %11}, %12, p, 1, 1, 0;\n}\n"
        : "+f"(d[0]), "+f"(d[1]), "+f"(d[2]), "+f"(d[3]), "+f"(d[4]), "+f"(d[5]), "+f"(d[6]), "+f"(d[7])
        : "r"(a0), "r"(a1), "r"(a2), "r"(a3), "l"(descB));
}

__device__ __forceinline__ void wgmma_rl_init(float (&d)[8], uint32_t a0, uint32_t a1, uint32_t a2, uint32_t a3, uint64_t descB) {
    asm volatile(
        "{\n.reg .pred p;\n"
        "setp.ne.b32 p, 0, 0;\n"
        "wgmma.mma_async.sync.aligned.m64n16k16.f32.bf16.bf16 "
        "{%0, %1, %2, %3, %4, %5, %6, %7}, "
        "{%8, %9, %10, %11}, %12, p, 1, 1, 0;\n}\n"
        : "=f"(d[0]), "=f"(d[1]), "=f"(d[2]), "=f"(d[3]), "=f"(d[4]), "=f"(d[5]), "=f"(d[6]), "=f"(d[7])
        : "r"(a0), "r"(a1), "r"(a2), "r"(a3), "l"(descB));
}


struct Item { int head; int grp; bool mc, rem; };
__device__ __forceinline__ Item decode_item(uint32_t e, int rank, int w) {
    Item it;
    e &= 0x7FF;
    it.mc = (e & 3) != 3;
    it.rem = !it.mc && (e >> 2 & 1) != w;
    it.head = it.mc ? e >> 2 : (e >> 3) * 2 + rank;
    it.grp = 32 * (e & 3) + (it.mc ? 16 * rank + 8 * w : it.rem ? 8 : 0);
    return it;
}
__device__ __forceinline__ uint32_t first_entry(uint32_t c) { return (c / 3) * 4 + c % 3; }

__device__ __forceinline__ uint32_t k_addr(int e) { return SM_K + ((e + KROT) & 3) * BLK_BYTES; }
__device__ __forceinline__ void next_v(uint32_t& v) { v = v == SM_V + 2 * BLK_BYTES ? SM_V : v + BLK_BYTES; }
__device__ __forceinline__ void wait_blocks(uint32_t sbase, int e) { mbar_wait(sbase + BAR_FULL + 8 * (e & 3), e >> 2 & 1); }
__device__ __forceinline__ uint64_t k_desc(int e) {
    return make_desc(((e + KROT) & 3) * (BLK_BYTES >> 4) + (((SM_BASE + SM_K) >> 4) | (1u << 16)), DESC_HI);
}
constexpr uint32_t V_DESC0 = ((SM_BASE + SM_V) >> 4) | ((SLAB_BYTES >> 4) << 16);
__device__ __forceinline__ void next_v_desc(uint32_t& v) { v = v == V_DESC0 + 2 * (BLK_BYTES >> 4) ? V_DESC0 : v + (BLK_BYTES >> 4); }
__device__ __forceinline__ constexpr uint32_t k_step(int k) { return (k & 3) == 3 ? (SLAB_BYTES >> 4) - 6 : 2; }

template <bool SPLIT>
__device__ __forceinline__ void issue_qk(float (&s)[32], uint32_t (&q)[48], int e) {
    fence_regs(q);
    wgmma_fence();
    uint64_t desc = k_desc(e);
#pragma unroll
    for (int k = 0; k < 12; k++) {
        if (k == 0) wgmma_qk_init(s, q[0], q[1], q[2], q[3], desc);
        else wgmma_qk(s, q[4 * k], q[4 * k + 1], q[4 * k + 2], q[4 * k + 3], desc);
        if (k < 11) desc += k_step(k);
        if (SPLIT && (k & 3) == 3) wgmma_commit();
    }
    if (!SPLIT) wgmma_commit();
}
template <bool FIRST, bool WAIT = true, bool FENCE = true>
__device__ __forceinline__ void issue_pv(float (&o)[96], uint32_t (&p)[16], uint32_t sbase, int b, uint32_t& v) {
    if (WAIT) wait_blocks(sbase, b + 2);
    if (!FIRST) fence_regs(o);
    fence_regs(p);
    if (FENCE) wgmma_fence();
    uint64_t desc = make_desc(v, DESC_HI);
#pragma unroll
    for (int k = 0; k < 4; k++) {
        if (FIRST && k == 0) wgmma_pv_init(o, p[0], p[1], p[2], p[3], desc);
        else wgmma_pv(o, p[4 * k], p[4 * k + 1], p[4 * k + 2], p[4 * k + 3], desc);
        if (k < 3) desc += 2 * GRP_BYTES >> 4;
    }
    wgmma_commit();
    next_v_desc(v);
}

__device__ __forceinline__ float opaque_copy(float x, uint32_t zero) { return x + __uint_as_float(zero); }

__device__ __forceinline__ float after(float x, float y, uint32_t zero) { return __uint_as_float(__float_as_uint(x) | (__float_as_uint(y) & zero)); }

template <bool FIRST>
__device__ __forceinline__ void exp_sum(float (&s)[32], float (&l)[2]) {
#pragma unroll
    for (int i = 0; i < 32; i++) s[i] = ex2(s[i]);
#pragma unroll
    for (int i = 0; i < 8; i++) {
        const float x = s[4 * i] + s[4 * i + 1], y = s[4 * i + 2] + s[4 * i + 3];
        if (FIRST && i == 0) { l[0] = x; l[1] = y; }
        else { l[0] += x; l[1] += y; }
    }
}
template <int LO, int HI>
__device__ __forceinline__ void exp_only(float (&s)[32]) {
#pragma unroll
    for (int i = LO; i < HI; i++) s[i] = ex2(s[i]);
}
__device__ __forceinline__ void sum_only(const float (&s)[32], float (&l)[2]) {
#pragma unroll
    for (int i = 0; i < 8; i++) { l[0] += s[4 * i] + s[4 * i + 1]; l[1] += s[4 * i + 2] + s[4 * i + 3]; }
}
__device__ __forceinline__ void pack_p(const float (&s)[32], uint32_t (&p)[16]) {
#pragma unroll
    for (int i = 0; i < 8; i++) {
        p[2 * i] = pack_bf16(s[4 * i], s[4 * i + 1]);
        p[2 * i + 1] = pack_bf16(s[4 * i + 2], s[4 * i + 3]);
    }
}
__device__ __forceinline__ bool sum_unsafe(float l) { return __float_as_uint(l) - SUM_LOW > SUM_HIGH - SUM_LOW; }

__device__ __forceinline__ void bb_boundary(uint32_t zero, float& x, float& y) {
    if (zero) {
#pragma unroll
        for (int i = 0; i < 12; i++) {
            asm volatile("mul.f32 %0, %0, %1;" : "+f"(x) : "f"(y));
            asm volatile("mul.f32 %0, %0, %1;" : "+f"(y) : "f"(x));
        }
    }
}
__device__ __forceinline__ void bb_boundary(uint32_t zero, float (&x)[2][2]) {
    if (zero) {
#pragma unroll
        for (int i = 0; i < 24; i++) asm volatile("mul.f32 %0, %0, %1;" : "+f"(x[i >> 1 & 1][i & 1]) : "f"(x[~i >> 1 & 1][i & 1]));
    }
}
__device__ __forceinline__ void bb_boundary(uint32_t zero, float (&x)[4]) {
    if (zero) {
#pragma unroll
        for (int i = 0; i < 24; i++) asm volatile("mul.f32 %0, %0, %1;" : "+f"(x[i & 3]) : "f"(x[(i + 2) & 3]));
    }
}
__device__ __forceinline__ uint32_t sched_fence() {
    uint32_t c;
    asm volatile("mov.u32 %0, %%clock;" : "=r"(c)::"memory");
    return c;
}
template <int CB>
__device__ __forceinline__ void load_q_slab(uint32_t (&q)[48], const uint32_t (&q_lane)[4]) {
#pragma unroll
    for (int k = 4 * CB; k < 4 * CB + 4; k++)
        ldsm_x4(q_lane[k & 3] + CB * SLAB_BYTES, q[4 * k], q[4 * k + 1], q[4 * k + 2], q[4 * k + 3]);
}
template <int LO, int HI, int STEP = 1>
__device__ __forceinline__ void scale_q(uint32_t (&q)[48]) {
#pragma unroll
    for (int i = LO; i < HI; i += STEP)
        asm("{\n.reg .b32 t;\nmul.rn.bf16x2 t, %0, %1;\nfma.rn.bf16x2 %0, %0, %2, t;\n}\n" : "+r"(q[i]) : "r"(SCALE_LO), "r"(SCALE_HI));
}
__device__ __forceinline__ void row_normalisers(float l0, float l1, float (&inv)[2][2], uint32_t& redo, uint32_t bit, uint32_t zero) {
    l0 += __shfl_xor_sync(0xffffffffu, l0, 1);
    l1 += __shfl_xor_sync(0xffffffffu, l1, 1);
    l0 += __shfl_xor_sync(0xffffffffu, l0, 2);
    l1 += __shfl_xor_sync(0xffffffffu, l1, 2);
    asm("rcp.approx.ftz.f32 %0, %1;" : "=f"(inv[0][0]) : "f"(l0));
    asm("rcp.approx.ftz.f32 %0, %1;" : "=f"(inv[1][0]) : "f"(l1));
    inv[0][1] = opaque_copy(inv[0][0], zero);
    inv[1][1] = opaque_copy(inv[1][0], zero);
    if (sum_unsafe(l0) | sum_unsafe(l1)) redo |= bit;
}
__device__ __forceinline__ void cvt_out(float (&o)[96], int k, const float (&inv)[2][2], uint32_t (&x)[4]) {
    float y[8];
#pragma unroll
    for (int i = 0; i < 8; i++) y[i] = o[8 * k + i] * inv[i >> 1 & 1][i & 1];
#pragma unroll
    for (int i = 0; i < 4; i++) x[i] = pack_bf16(y[2 * i], y[2 * i + 1]);
}
template <int K0, int K1, bool GAPS>
__device__ __forceinline__ void stage_output(float (&o)[96], const float (&inv)[2][2], const uint32_t (&q_lane)[4]) {
#pragma unroll
    for (int k = K0; k < K1; k++) {
        uint32_t x[4];
        cvt_out(o, k, inv, x);
        if (GAPS) wgmma_wait<0>();
        stsm_x4(q_lane[k & 3] + (k >> 2) * SLAB_BYTES, x[0], x[1], x[2], x[3]);
    }
}
template <int K0>
__device__ __forceinline__ void issue_qk_stage(float (&s)[32], uint32_t (&q)[48], int e, float (&o)[96], float (&inv)[2][2], const uint32_t (&q_lane)[4],
                                               uint32_t& keep) {
    constexpr int NS = 12 - K0;
    uint32_t x[NS][4];
#pragma unroll
    for (int j = 0; j < STG_N1; j++) cvt_out(o, K0 + j, inv, x[j]);
    fence_regs(q);
    wgmma_fence();
    uint64_t desc = k_desc(e);
#pragma unroll
    for (int k = 0; k < 12; k++) {
        if (k == 0) wgmma_qk_init(s, q[0], q[1], q[2], q[3], desc);
        else wgmma_qk(s, q[4 * k], q[4 * k + 1], q[4 * k + 2], q[4 * k + 3], desc);
        if (k < 11) desc += k_step(k);
        if (k == STG_CVTK) {
            keep &= sched_fence();
            fence_regs(inv[0]); fence_regs(inv[1]);
#pragma unroll
            for (int j = STG_N1; j < NS; j++) cvt_out(o, K0 + j, inv, x[j]);
        }
#pragma unroll
        for (int j = 0; j < NS; j++)
            if (k == (STG_POS >> 4 * j & 15)) stsm_x4(q_lane[(K0 + j) & 3] + ((K0 + j) >> 2) * SLAB_BYTES, x[j][0], x[j][1], x[j][2], x[j][3]);
    }
    wgmma_commit();
}
__device__ __forceinline__ void publish_output(uint32_t oready, int lane) {
    fence_async_smem();
    __syncwarp();
    mbar_arrive_pred(oready, lane == 0);
}

__device__ __forceinline__ void stsm_x4_t(uint32_t addr, uint32_t r0, uint32_t r1, uint32_t r2, uint32_t r3) {
    asm volatile("stmatrix.sync.aligned.m8n8.x4.trans.shared.b16 [%0], {%1, %2, %3, %4};" ::"r"(addr), "r"(r0), "r"(r1), "r"(r2), "r"(r3) : "memory");
}
__device__ __forceinline__ void issue_rem_qk(float (&s)[8], int e) {
    uint64_t da = k_desc(e), db = make_desc(((SM_BASE + SM_REM) >> 4) | (1u << 16), DESC_HI);
#pragma unroll
    for (int k = 0; k < 12; k++) {
        if (k == 0) wgmma_rk_init(s, da, db);
        else wgmma_rk(s, da, db);
        if (k < 11) { da += k_step(k); db += k_step(k); }
    }
    wgmma_commit();
}
constexpr uint32_t PT_DESC_HI = (1024 >> 4) | (1u << 30);
__device__ __forceinline__ void issue_rem_pv(float (&o)[3][8], uint32_t pt, uint32_t& v) {
    const uint64_t da = make_desc(v, DESC_HI), db = make_desc(pt * (2048 >> 4) + (((SM_BASE + SM_PT) >> 4) | (1u << 16)), PT_DESC_HI);
#pragma unroll
    for (int k = 0; k < 4; k++)
#pragma unroll
        for (int m = 0; m < 3; m++) wgmma_rv(o[m], da + k * (2 * GRP_BYTES >> 4) + m * (SLAB_BYTES >> 4), db + 2 * k);
    wgmma_commit();
    next_v_desc(v);
}
__device__ __forceinline__ void rem_softmax(float (&s)[8], float (&l)[4]) {
#pragma unroll
    for (int i = 0; i < 8; i++) s[i] = ex2(s[i] * SCALE_LOG2E);
    l[0] += s[0] + s[2]; l[1] += s[1] + s[3]; l[2] += s[4] + s[6]; l[3] += s[5] + s[7];
}
__device__ __forceinline__ void rem_store(const float (&s)[8], uint32_t addr) {
    stsm_x4_t(addr, pack_bf16(s[0], s[1]), pack_bf16(s[2], s[3]), pack_bf16(s[4], s[5]), pack_bf16(s[6], s[7]));
}

__device__ __forceinline__ void mma_16816(float (&c)[4], uint32_t a0, uint32_t a1, uint32_t a2, uint32_t a3, uint32_t b0, uint32_t b1) {
    asm volatile("mma.sync.aligned.m16n8k16.row.col.f32.bf16.bf16.f32 {%0, %1, %2, %3}, {%4, %5, %6, %7}, {%8, %9}, {%0, %1, %2, %3};"
                 : "+f"(c[0]), "+f"(c[1]), "+f"(c[2]), "+f"(c[3]) : "r"(a0), "r"(a1), "r"(a2), "r"(a3), "r"(b0), "r"(b1));
}
__device__ __forceinline__ void exact_rows(const uint4* __restrict__ gq, const uint4* __restrict__ gk, const uint4* __restrict__ gv, uint4* __restrict__ go,
                                           int head, int row0, int lane) {
    constexpr int R = ROW_BYTES / 16;
    const int g = lane >> 2, c = lane & 3;
    const uint4* pq = gq + ((size_t)head * SQ + row0 + g) * R + c;
    uint4 qa[6], qb[6];
#pragma unroll
    for (int k = 0; k < 6; k++) { qa[k] = __ldg(pq + 4 * k); qb[k] = __ldg(pq + 8 * R + 4 * k); }
    float o[24][4], m[2] = {-INFINITY, -INFINITY}, l[2] = {0.f, 0.f};
#pragma unroll
    for (int i = 0; i < 24; i++) o[i][0] = o[i][1] = o[i][2] = o[i][3] = 0.f;
#pragma unroll 1
    for (int key0 = 0; key0 < SK; key0 += 16) {
        float s[2][4];
#pragma unroll
        for (int j = 0; j < 2; j++) {
            s[j][0] = s[j][1] = s[j][2] = s[j][3] = 0.f;
            const uint4* pk = gk + ((size_t)head * SK + key0 + 8 * j + g) * R + c;
#pragma unroll
            for (int k = 0; k < 6; k++) {
                const uint4 x = __ldg(pk + 4 * k);
                mma_16816(s[j], qa[k].x, qb[k].x, qa[k].y, qb[k].y, x.x, x.y);
                mma_16816(s[j], qa[k].z, qb[k].z, qa[k].w, qb[k].w, x.z, x.w);
            }
        }
#pragma unroll
        for (int h = 0; h < 2; h++) {
            float f = fmaxf(fmaxf(s[0][2 * h], s[0][2 * h + 1]), fmaxf(s[1][2 * h], s[1][2 * h + 1]));
            f = fmaxf(f, __shfl_xor_sync(0xffffffffu, f, 1));
            f = fmaxf(f, __shfl_xor_sync(0xffffffffu, f, 2));
            f = fmaxf(f, m[h]);
            const float ref = f == -INFINITY ? 0.f : f;
            const float sc = ex2((m[h] - ref) * SCALE_LOG2E);
            m[h] = f;
            l[h] *= sc;
#pragma unroll
            for (int j = 0; j < 2; j++)
#pragma unroll
                for (int e = 0; e < 2; e++) { s[j][2 * h + e] = ex2((s[j][2 * h + e] - ref) * SCALE_LOG2E); l[h] += s[j][2 * h + e]; }
#pragma unroll
            for (int i = 0; i < 24; i++) { o[i][2 * h] *= sc; o[i][2 * h + 1] *= sc; }
        }
        const uint32_t a0 = pack_bf16(s[0][0], s[0][1]), a1 = pack_bf16(s[0][2], s[0][3]), a2 = pack_bf16(s[1][0], s[1][1]), a3 = pack_bf16(s[1][2], s[1][3]);
        const uint4* pv = gv + ((size_t)head * SK + key0 + 2 * c) * R + g;
#pragma unroll
        for (int sl = 0; sl < 3; sl++) {
            const uint4 v0 = __ldg(pv + 8 * sl), v1 = __ldg(pv + R + 8 * sl), v2 = __ldg(pv + 8 * R + 8 * sl), v3 = __ldg(pv + 9 * R + 8 * sl);
            const uint32_t w0[4] = {v0.x, v0.y, v0.z, v0.w}, w1[4] = {v1.x, v1.y, v1.z, v1.w}, w2[4] = {v2.x, v2.y, v2.z, v2.w}, w3[4] = {v3.x, v3.y, v3.z, v3.w};
#pragma unroll
            for (int i = 0; i < 8; i++)
                mma_16816(o[8 * sl + i], a0, a1, a2, a3, __byte_perm(w0[i >> 1], w1[i >> 1], (i & 1) ? 0x7632 : 0x5410),
                          __byte_perm(w2[i >> 1], w3[i >> 1], (i & 1) ? 0x7632 : 0x5410));
        }
    }
#pragma unroll
    for (int h = 0; h < 2; h++) {
        l[h] += __shfl_xor_sync(0xffffffffu, l[h], 1);
        l[h] += __shfl_xor_sync(0xffffffffu, l[h], 2);
        const float inv = 1.0f / l[h];
        uint4* po = go + ((size_t)head * SQ + row0 + 8 * h + g) * R + 2 * c;
#pragma unroll
        for (int sl = 0; sl < 3; sl++)
#pragma unroll
            for (int e = 0; e < 2; e++) {
                uint32_t w[4];
#pragma unroll
                for (int i = 0; i < 4; i++) w[i] = pack_bf16(o[8 * sl + 2 * i][2 * h + e] * inv, o[8 * sl + 2 * i + 1][2 * h + e] * inv);
                po[8 * sl + e] = make_uint4(w[0], w[1], w[2], w[3]);
            }
    }
}

#define ROLE_SETUP()                                                                          \
    uint32_t bid_;                                                                            \
    asm volatile("mov.u32 %0, %%ctaid.x;" : "=r"(bid_));                                      \
    const uint32_t rank = bid_ & 1;                                                           \
    const int cluster_id = bid_ >> 1;                                                         \
    const uint16_t* sched = SCHED[cluster_id];

__device__ __forceinline__ void consumer(const uint32_t sbase, const int warp_idx, const int lane, const uint32_t zero, const uint4* __restrict__ gq,
                                         const uint4* __restrict__ gk, const uint4* __restrict__ gv, uint4* __restrict__ go) {
    ROLE_SETUP()
    const int wg = (warp_idx >> 2) - 1;
    const int tw = threadIdx.x & 127;
    const int bar_me = __shfl_sync(0xffffffffu, 1 + wg + (lane & zero), lane), bar_other = __shfl_sync(0xffffffffu, 2 - wg + (lane & zero), lane);
    const uint32_t qo = sbase + SM_QO + wg * BLK_BYTES + (warp_idx & 3) * 2 * GRP_BYTES;
    uint32_t q_lane[4];
#pragma unroll
    for (int i = 0; i < 4; i++)
        q_lane[i] = __shfl_sync(0xffffffffu, (qo + (lane & 7) * 128 + ((lane >> 3) & 1) * GRP_BYTES + (((lane >> 4) ^ (lane & 7)) << 4)) ^ (i * 32), lane);
    const uint32_t qfull = sbase + BAR_QFULL + 8 * wg, oready = sbase + BAR_OREADY + 8 * wg;

    float o[96], s[32], l[2];
    uint32_t q[48], p[16];
    uint32_t redo = 0;
    uint32_t v = V_DESC0;
    const uint32_t rel_pred = (tw == 0 || tw == 32) ? 1u : 0u;
    const uint32_t rel_base = __shfl_sync(0xffffffffu, mapa(sbase, warp_idx & 1) + BAR_DONE, 0);
    auto release = [&](int e) { mbar_arrive_cluster_pred(rel_base + 8 * (e & 3), rel_pred); };

    if (wg == 1) bar_arrive(1, 256);

    mbar_wait(qfull, 0);
    load_q_slab<0>(q, q_lane); load_q_slab<1>(q, q_lane); load_q_slab<2>(q, q_lane);
    scale_q<0, 48>(q);
    wait_blocks(sbase, 0);
    bar_sync(bar_me, 256);
    issue_qk<false>(s, q, 0);
    bar_arrive(bar_other, 256);
    const int n_items = sched[SCHED_COUNT];
    const uint32_t breaks = __shfl_sync(0xffffffffu, reinterpret_cast<const uint32_t*>(sched + SCHED_BREAKS)[wg], 0);
    wgmma_wait<0>();
    fence_regs(s);
    release(0);
    exp_sum<true>(s, l);
    pack_p(s, p);
    wait_blocks(sbase, 1);
    wait_blocks(sbase, 2);
    float inv[2][2] = {{0.f, 0.f}, {0.f, 0.f}};
    forget(o);

    auto phase_tail = [&](int b) {
        exp_sum<false>(s, l);
        fence_regs(s);
        mbar_wait(sbase + BAR_DUMMY, 1);
        wgmma_wait<0>();
        fence_regs(o);
        fence_regs(p);
        release(b + 1);
        pack_p(s, p);
    };

    for (int t = 0;; t++) {
        const bool has_next = t + 1 < n_items, chain = !(breaks >> t & 2);
        bar_sync(bar_me, 256);
        uint32_t keep = zero;
        issue_qk_stage<STAGE_SPLIT>(s, q, 1, o, inv, q_lane, keep);
        issue_pv<true, false>(o, p, sbase, 0, v);
        bar_arrive(bar_other, 256);
        wgmma_wait<1>();
        fence_regs(s);
        phase_tail(0);
        redo |= keep & p[15];
#pragma unroll 1
        for (int b = 1; b < NBLK - 2; b++) {
            bar_sync(bar_me, 256);
            issue_qk<false>(s, q, b + 1);
            if (b == PUB_B) publish_output(oready, lane);
            issue_pv<false>(o, p, sbase, b, v);
            bar_arrive(bar_other, 256);
            wgmma_wait<1>();
            fence_regs(s);
            phase_tail(b);
        }
        uint32_t c[8];
        mbar_wait(qfull, ~t & 1);
        bar_sync(bar_me, 256);
        issue_qk<true>(s, q, 7);
        wait_blocks(sbase, 8);
        wgmma_wait<2>();
        load_q_slab<0>(q, q_lane);
        issue_pv<false, false>(o, p, sbase, 6, v);
        bar_arrive(bar_other, 256);
        c[0] = sched_fence();
        wgmma_wait<2>();
        scale_q<0, 16, 4>(q);
        fence_regs(q);
        c[1] = sched_fence();
        load_q_slab<1>(q, q_lane);
        c[2] = sched_fence();
        wgmma_wait<1>();
        fence_regs(s);
        exp_only<0, P6N>(s);
        scale_q<1, 16, 4>(q); scale_q<2, 16, 4>(q); scale_q<3, 16, 4>(q);
        fence_regs(s); fence_regs(q);
        c[3] = sched_fence();
        scale_q<16, 32, 4>(q);
        fence_regs(q);
        c[4] = sched_fence();
        load_q_slab<2>(q, q_lane);
        c[5] = sched_fence();
        uint32_t p7[16];
        exp_only<P6N, 32>(s);
        scale_q<17, 32, 4>(q); scale_q<18, 32, 4>(q); scale_q<19, 32, 4>(q);
        fence_regs(s); fence_regs(q); fence_regs(l);
        c[6] = sched_fence();
        wgmma_wait<0>();
        fence_regs(o);
        fence_regs(p);
        release(7);
        sum_only(s, l);
        pack_p(s, p7);
        fence_regs(p7);
        c[7] = sched_fence();
        scale_q<32, 48>(q);
        redo |= c[0] & c[1] & c[2] & c[3] & c[4] & c[5] & c[6] & c[7] & zero;
        if (chain) {
            bar_sync(bar_me, 256);
            issue_qk<false>(s, q, 0);
            issue_pv<false>(o, p7, sbase, 7, v);
            bar_arrive(bar_other, 256);
            wgmma_wait<1>();
            fence_regs(s);
            row_normalisers(after(l[0], s[30], zero), after(l[1], s[31], zero), inv, redo, 1u << t, zero);
            exp_sum<true>(s, l);
            pack_p(s, p);
            fence_regs(p);
            fence_regs(s); fence_regs(l);
            wait_blocks(sbase, 10);
            wgmma_wait<0>();
            fence_regs(o);
            fence_regs(p7);
            release(8);
            stage_output<0, STAGE_SPLIT, true>(o, inv, q_lane);
            continue;
        }
        if (!has_next) {
            bar_sync(bar_me, 256);
            issue_pv<false>(o, p7, sbase, 7, v);
            if ((int)breaks < 0) bar_arrive(bar_other, 256);
            row_normalisers(l[0], l[1], inv, redo, 1u << t, zero);
            wgmma_wait<0>();
            fence_regs(o);
            stage_output<0, 12, true>(o, inv, q_lane);
            break;
        }
        float rs[8], rs0[8];
        bar_sync(bar_me, 256);
        fence_regs(o); fence_regs(p7);
        wgmma_fence();
        issue_rem_qk(rs0, 0);
        issue_pv<false, false, false>(o, p7, sbase, 7, v);
        issue_rem_qk(rs, 1);
        bar_arrive(bar_other, 256);
        const uint32_t t_lane = sbase + (lane & 7) * 128 + ((((warp_idx & 3) * 2 + (lane >> 3 & 1)) ^ (lane & 7)) << 4);
        const uint32_t pt_lane = t_lane + SM_PT + (lane >> 4) * 1024;
        float ro[3][8], rl[4] = {0.f, 0.f, 0.f, 0.f};
        bb_boundary(zero, l[0], l[1]);
        row_normalisers(l[0], l[1], inv, redo, 1u << t, zero);
        t++;
        bb_boundary(zero, inv);
        wgmma_wait<1>();
        fence_regs(rs0); fence_regs(o);
        release(0);
        rem_softmax(rs0, rl);
        rem_store(rs0, pt_lane);
        bb_boundary(zero, rl);
        wgmma_wait<0>();
        fence_regs(rs);
        rem_softmax(rs, rl);
        rem_store(rs, pt_lane + 2048);
        fence_async_smem();
        mbar_arrive_pred(qfull, tw == 0);
#pragma unroll
        for (int i = 0; i < 8; i++) ro[0][i] = ro[1][i] = ro[2][i] = 0.f;
#pragma unroll 1
        for (int b = 0;; b++) {
            bar_sync(bar_me, 256);
            fence_regs(ro[0]); fence_regs(ro[1]); fence_regs(ro[2]);
            wgmma_fence();
            issue_rem_qk(rs, b + 2);
            issue_rem_pv(ro, b & 1, v);
            bar_arrive(bar_other, 256);
            wgmma_wait<1>();
            fence_regs(rs);
            rem_softmax(rs, rl);
            fence_regs(rs);
            bb_boundary(zero, rl[0], rl[1]);
            wgmma_wait<0>();
            fence_regs(ro[0]); fence_regs(ro[1]); fence_regs(ro[2]);
            release(b + 1);
            bar_sync(3, 128);
            rem_store(rs, pt_lane + (b & 1) * 2048);
            if (b == NBLK - 3) break;
            fence_async_smem();
            if (b == MS0) stage_output<0, STAGE_SPLIT / 4, false>(o, inv, q_lane);
            if (b == MS0 + 1) stage_output<STAGE_SPLIT / 4, STAGE_SPLIT / 2, false>(o, inv, q_lane);
            if (b == MS0 + 2) stage_output<STAGE_SPLIT / 2, STAGE_SPLIT * 3 / 4, false>(o, inv, q_lane);
            if (b == MS0 + 3) stage_output<STAGE_SPLIT * 3 / 4, STAGE_SPLIT, false>(o, inv, q_lane);
        }
        {
            const uint32_t h0 = pack_bf16(rl[0], rl[1]), h1 = pack_bf16(rl[2], rl[3]);
            stsm_x4_t(pt_lane + (SM_REM - SM_PT), h0, pack_bf16(rl[0] - __uint_as_float(h0 << 16), rl[1] - __uint_as_float(h0 & 0xffff0000u)),
                      h1, pack_bf16(rl[2] - __uint_as_float(h1 << 16), rl[3] - __uint_as_float(h1 & 0xffff0000u)));
        }
        fence_async_smem();
        uint32_t ones[4] = {0x3F803F80u, 0x3F803F80u, 0x3F803F80u, 0x3F803F80u};
        auto rem_last = [&]() {
            wgmma_commit();
            issue_rem_pv(ro, 0, v);
            wait_blocks(sbase, 9);
            fence_regs(ro[0]); fence_regs(ro[1]); fence_regs(ro[2]);
            wgmma_fence();
            issue_rem_pv(ro, 1, v);
            bar_arrive(bar_other, 256);
            wgmma_wait<2>();
            fence_regs(rs);
            mbar_arrive_pred(sbase + BAR_SUMS, lane == 0);
            if (sum_unsafe(rs[0]) | sum_unsafe(rs[1]) | sum_unsafe(rs[4]) | sum_unsafe(rs[5])) redo |= 1u << t;
#pragma unroll
            for (int i = 0; i < 4; i++) asm("rcp.approx.ftz.f32 %0, %1;" : "=f"(rl[i]) : "f"(rs[(i & 2) * 2 + (i & 1)]));
        };
        auto rem_stage = [&]() {
            mbar_wait(sbase + BAR_SUMS, wg ^ 1);
            wgmma_wait<0>();
            fence_regs(ro[0]); fence_regs(ro[1]); fence_regs(ro[2]);
            release(7);
            release(0);
#pragma unroll
            for (int m = 0; m < 3; m++)
                stsm_x4_t(t_lane + SM_REM + (lane >> 4) * GRP_BYTES + m * SLAB_BYTES, pack_bf16(ro[m][0] * rl[0], ro[m][1] * rl[1]), pack_bf16(ro[m][2] * rl[0], ro[m][3] * rl[1]),
                          pack_bf16(ro[m][4] * rl[2], ro[m][5] * rl[3]), pack_bf16(ro[m][6] * rl[2], ro[m][7] * rl[3]));
        };
        const uint64_t sum_desc = make_desc(((SM_BASE + SM_REM) >> 4) | (1u << 16), PT_DESC_HI);
        fence_regs(ones);
        bar_sync(bar_me, 256);
        fence_regs(ro[0]); fence_regs(ro[1]); fence_regs(ro[2]);
        if (t + 1 == n_items) {
            wgmma_fence();
            wgmma_rl_init(rs, ones[0], ones[1], ones[2], ones[3], sum_desc);
#pragma unroll
            for (int k = 1; k < 4; k++) wgmma_rl(rs, ones[0], ones[1], ones[2], ones[3], sum_desc + 2 * k);
            rem_last();
            stage_output<STAGE_SPLIT, 12, false>(o, inv, q_lane);
            rem_stage();
            break;
        }
        fence_regs(q);
        wgmma_fence();
        {
            uint64_t desc = k_desc(0);
#pragma unroll
            for (int k = 0; k < 12; k++) {
                if (k == 0) wgmma_qk_init(s, q[0], q[1], q[2], q[3], desc);
                else wgmma_qk(s, q[4 * k], q[4 * k + 1], q[4 * k + 2], q[4 * k + 3], desc);
                if (k < 11) desc += k_step(k);
                if (k == SK0) wgmma_rl_init(rs, ones[0], ones[1], ones[2], ones[3], sum_desc);
#pragma unroll
                for (int j = 1; j < 4; j++)
                    if (k == SK0 + j * SDK) wgmma_rl(rs, ones[0], ones[1], ones[2], ones[3], sum_desc + 2 * j);
            }
        }
        rem_last();
        fence_regs(s);
        exp_sum<true>(s, l);
        pack_p(s, p);
        rem_stage();
        wait_blocks(sbase, 2);
    }
    redo = __reduce_or_sync(0xffffffffu, redo);
    if (redo) asm volatile("st.shared.u32 [%0], %1;" ::"r"(sbase + SM_REDO + 4 * wg), "r"(1) : "memory");
    publish_output(oready, lane);
    if (redo) {
        mbar_wait(sbase + BAR_STORED + 8 * wg, 0);
        asm volatile("fence.proxy.async;" ::: "memory");
        for (; redo; redo &= redo - 1) {
            const Item it = decode_item(sched[__ffs(redo) - 1], rank, wg);
            const int row0 = it.grp * 8 + (warp_idx & 3) * 16;
            if (row0 < SQ) exact_rows(gq, gk, gv, go, it.head, row0, lane);
        }
    }
}

__global__ void __cluster_dims__(2, 1, 1) __launch_bounds__(384, 1)
attn_fwd_kernel(const __grid_constant__ CUtensorMap tmQ, const __grid_constant__ CUtensorMap tmK, const __grid_constant__ CUtensorMap tmV,
                const __grid_constant__ CUtensorMap tmO, const __grid_constant__ CUtensorMap tmR, const uint32_t zero,
                const uint4* __restrict__ gq, const uint4* __restrict__ gk, const uint4* __restrict__ gv, uint4* __restrict__ go) {
    extern __shared__ __align__(1024) uint8_t smem_raw[];
    const uint32_t sbase = smem_u32(smem_raw);
    const int warp_idx = __shfl_sync(0xffffffffu, threadIdx.x >> 5, 0);
    const int lane = threadIdx.x & 31;

    if (threadIdx.x == 0) {
        if ((sbase & 0x3FFFF) != SM_BASE) __trap();
        for (int i = 0; i < 4; i++) { mbar_init(sbase + BAR_FULL + 8 * i, 1); mbar_init(sbase + BAR_DONE + 8 * i, 4); }
        for (int i = 0; i < 2; i++) { mbar_init(sbase + BAR_QFULL + 8 * i, 1); mbar_init(sbase + BAR_OREADY + 8 * i, 4); mbar_init(sbase + BAR_STORED + 8 * i, 1); }
        mbar_init(sbase + BAR_DUMMY, 1);
        mbar_init(sbase + BAR_REMFREE, 1);
        mbar_init(sbase + BAR_SUMS, 4);
        asm volatile("st.shared.v2.u32 [%0], {%1, %1};" ::"r"(sbase + SM_REDO), "r"(0) : "memory");
        asm volatile("fence.mbarrier_init.release.cluster;" ::: "memory");
    } else if (threadIdx.x == 32) {
        asm volatile("prefetch.tensormap [%0];" ::"l"(&tmQ) : "memory");
        asm volatile("prefetch.tensormap [%0];" ::"l"(&tmK) : "memory");
        asm volatile("prefetch.tensormap [%0];" ::"l"(&tmV) : "memory");
        asm volatile("prefetch.tensormap [%0];" ::"l"(&tmO) : "memory");
        asm volatile("prefetch.tensormap [%0];" ::"l"(&tmR) : "memory");
    }
    __syncthreads();
    asm volatile("barrier.cluster.arrive.relaxed.aligned;" ::: "memory");
    if (warp_idx < 3 && (int)(blockIdx.x >> 1) < EARLY_CLUSTERS) {
        if (elect_one()) {
            const int w = warp_idx - 1;
            const Item q = decode_item(first_entry(blockIdx.x >> 1), blockIdx.x & 1, w);
            if (warp_idx == 0) {
                mbar_expect_tx(sbase + BAR_FULL, BLK_BYTES);
                tma_load_kv(sbase + k_addr(0), &tmK, q.head * (SK / 8), sbase + BAR_FULL);
            } else {
                mbar_expect_tx(sbase + BAR_QFULL + 8 * w, BLK_BYTES);
                tma_load_q(sbase + SM_QO + w * BLK_BYTES, &tmQ, q.grp, q.head, sbase + BAR_QFULL + 8 * w);
            }
        }
        __syncwarp();
    }
    asm volatile("barrier.cluster.wait.aligned;" ::: "memory");

    if (warp_idx < 4) {
        asm volatile("setmaxnreg.dec.sync.aligned.u32 %0;" ::"n"(PRODUCER_REGS));
        ROLE_SETUP()
        if (cluster_id >= EARLY_CLUSTERS) {
            const uint32_t t0 = clock(), d = (cluster_id - EARLY_CLUSTERS + 1) * START_STEP;
            while ((uint32_t)clock() - t0 < d) __nanosleep(20);
        }
        if (warp_idx == 0) {
            if (elect_one()) {
                auto load = [&](const CUtensorMap* tm, uint32_t owner, const Item& it, int blk, uint32_t dst, uint32_t full) {
                    const int grp = it.head * (SK / 8) + blk * 8;
                    if (!it.mc) tma_load_kv(sbase + dst, tm, grp, full);
                    else if (rank == owner) tma_load_kv_mc(sbase + dst, tm, grp, full);
                };
                Item iv = decode_item(first_entry(cluster_id), rank, 0), ik = iv;
                for (int e = cluster_id < EARLY_CLUSTERS; e < 2; e++) {
                    mbar_expect_tx(sbase + BAR_FULL + 8 * e, BLK_BYTES);
                    load(&tmK, 0, ik, e, k_addr(e), sbase + BAR_FULL + 8 * e);
                }
                uint32_t v = SM_V;
                bool more = true;
                for (int t = 1; more; t++) {
#pragma unroll 1
                    for (int e = 2; e < NBLK + 2; e++) {
                        if (e == NBLK) { more = t < sched[SCHED_COUNT]; ik = decode_item(sched[t], rank, 0); }
                        const uint32_t full = sbase + BAR_FULL + 8 * (e & 3);
                        mbar_sleep(full + (BAR_DONE - BAR_FULL), ~e >> 2 & 1);
                        mbar_expect_tx(full, more ? 2 * BLK_BYTES : BLK_BYTES);
                        load(&tmV, 1, iv, e - 2, v, full);
                        if (more) load(&tmK, 0, ik, e & 7, k_addr(e), full);
                        next_v(v);
                    }
                    iv = ik;
                }
            }
        } else if (warp_idx < 3) {
            if (elect_one()) {
                const int w = warp_idx - 1;
                const uint32_t buf = sbase + SM_QO + w * BLK_BYTES;
                const uint32_t qfull = sbase + BAR_QFULL + 8 * w, oready = sbase + BAR_OREADY + 8 * w;
                if (cluster_id >= EARLY_CLUSTERS) {
                    const Item q = decode_item(first_entry(cluster_id), rank, w);
                    mbar_expect_tx(qfull, BLK_BYTES);
                    tma_load_q(buf, &tmQ, q.grp, q.head, qfull);
                }
                const int n_items = sched[SCHED_COUNT];
                for (int r = 0, phase = 0; r <= n_items; r++, phase ^= 1) {
                    mbar_sleep(oready, phase);
                    for (const uint32_t t1 = clock() + (sched[r] >> 11) * 128; (int)(clock() - t1) < 0;) __nanosleep(50);
                    const Item rq = decode_item(sched[r + 1], rank, w), q = decode_item(sched[r + 1 + rq.rem], rank, w);
                    const Item ro = decode_item(sched[r > 0 ? r - 1 : 0], rank, w), o = decode_item(sched[r > 0 ? r - 1 - ro.rem : 0], rank, w);
                    if (r > 0) {
                        tma_store_o(&tmO, buf, o.grp, o.head);
                        if (ro.rem) tma_store_o(&tmO, sbase + SM_REM, ro.grp, ro.head);
                        bulk_commit();
                        bulk_wait_read();
                        if (ro.rem) mbar_arrive(sbase + BAR_REMFREE);
                    }
                    if (r < n_items) {
                        const bool full = r + 1 + rq.rem < n_items;
                        mbar_expect_tx(qfull, (rq.rem ? REM_BYTES : 0) + (full ? BLK_BYTES : 0));
                        if (full) tma_load_q(buf, &tmQ, q.grp, q.head, qfull);
                        if (rq.rem) {
                            mbar_sleep(sbase + BAR_REMFREE, w);
                            tma_load_q(sbase + SM_REM, &tmR, rq.grp, rq.head, qfull);
                        }
                        r += rq.rem;
                    }
                }
                uint32_t redo;
                asm volatile("ld.shared.u32 %0, [%1];" : "=r"(redo) : "r"(sbase + SM_REDO + 4 * w) : "memory");
                if (redo) {
                    asm volatile("cp.async.bulk.wait_group 0;\nfence.proxy.async;" ::: "memory");
                    mbar_arrive(sbase + BAR_STORED + 8 * w);
                }
            }
        }
        else if (T_KVPF && elect_one()) {
            const int n_items = sched[SCHED_COUNT];
            const char* kv = reinterpret_cast<const char*>(rank ? gv : gk);
#pragma unroll 1
            for (int e = 4; e < NBLK * n_items; e++) {
                mbar_sleep(sbase + BAR_DONE + 8 * (e & 3), ~e >> 2 & 1);
                const int x = e + T_KVPF - 2 * rank;
                const uint32_t it = sched[x >> 3] & 0x7FF;
                if (x >> 3 < n_items && (it & 3) != 3)
                    asm volatile("cp.async.bulk.prefetch.L2.global [%0], %1;" ::"l"(kv + ((it >> 2) * 24 + (x & 7) * 3 + (it & 3)) * (BLK_BYTES / 3)), "r"(BLK_BYTES / 3) : "memory");
            }
        }
    } else {
        asm volatile("setmaxnreg.inc.sync.aligned.u32 %0;" ::"n"(CONSUMER_REGS));
        consumer(sbase, warp_idx, lane, zero, gq, gk, gv, go);
    }
    asm volatile("barrier.cluster.arrive.relaxed.aligned;\nbarrier.cluster.wait.aligned;" ::: "memory");
}

typedef CUresult (*EncodeTiledFn)(CUtensorMap*, CUtensorMapDataType, cuuint32_t, void*, const cuuint64_t*, const cuuint64_t*,
                                  const cuuint32_t*, const cuuint32_t*, CUtensorMapInterleave, CUtensorMapSwizzle,
                                  CUtensorMapL2promotion, CUtensorMapFloatOOBfill);

}

extern "C" void kernel_launch(void* const* d_in, const int* in_sizes, int n_in, void* d_out, int out_size) {
    (void)in_sizes; (void)n_in; (void)out_size;
    static CUtensorMap tmQ, tmK, tmV, tmO, tmR;
    static void* cached[4] = {nullptr, nullptr, nullptr, nullptr};
    if (cached[0] != d_in[0] || cached[1] != d_in[1] || cached[2] != d_in[2] || cached[3] != d_out) {
        void* fn = nullptr;
        cudaDriverEntryPointQueryResult qr;
        cudaGetDriverEntryPoint("cuTensorMapEncodeTiled", &fn, cudaEnableDefault, &qr);
        EncodeTiledFn enc = (EncodeTiledFn)fn;
        const cuuint32_t es[5] = {1, 1, 1, 1, 1};
        const cuuint32_t box[5] = {64, 8, 3, 8, 1};
        const cuuint32_t box_rem[5] = {64, 8, 3, 2, 1};
        {
            cuuint64_t gd[5] = {64, 8, 3, SQ / 8, NHEADS};
            cuuint64_t gs[4] = {ROW_BYTES, 128, 8 * ROW_BYTES, (cuuint64_t)SQ * ROW_BYTES};
            enc(&tmQ, CU_TENSOR_MAP_DATA_TYPE_BFLOAT16, 5, d_in[0], gd, gs, box, es, CU_TENSOR_MAP_INTERLEAVE_NONE,
                CU_TENSOR_MAP_SWIZZLE_128B, CU_TENSOR_MAP_L2_PROMOTION_NONE, CU_TENSOR_MAP_FLOAT_OOB_FILL_NONE);
            enc(&tmR, CU_TENSOR_MAP_DATA_TYPE_BFLOAT16, 5, d_in[0], gd, gs, box_rem, es, CU_TENSOR_MAP_INTERLEAVE_NONE,
                CU_TENSOR_MAP_SWIZZLE_128B, CU_TENSOR_MAP_L2_PROMOTION_NONE, CU_TENSOR_MAP_FLOAT_OOB_FILL_NONE);
            enc(&tmO, CU_TENSOR_MAP_DATA_TYPE_BFLOAT16, 5, d_out, gd, gs, box, es, CU_TENSOR_MAP_INTERLEAVE_NONE,
                CU_TENSOR_MAP_SWIZZLE_128B, CU_TENSOR_MAP_L2_PROMOTION_NONE, CU_TENSOR_MAP_FLOAT_OOB_FILL_NONE);
        }
        {
            cuuint64_t gd[4] = {64, 8, 3, (cuuint64_t)NHEADS * SK / 8};
            cuuint64_t gs[3] = {ROW_BYTES, 128, 8 * ROW_BYTES};
            enc(&tmK, CU_TENSOR_MAP_DATA_TYPE_BFLOAT16, 4, d_in[1], gd, gs, box, es, CU_TENSOR_MAP_INTERLEAVE_NONE,
                CU_TENSOR_MAP_SWIZZLE_128B, CU_TENSOR_MAP_L2_PROMOTION_NONE, CU_TENSOR_MAP_FLOAT_OOB_FILL_NONE);
            enc(&tmV, CU_TENSOR_MAP_DATA_TYPE_BFLOAT16, 4, d_in[2], gd, gs, box, es, CU_TENSOR_MAP_INTERLEAVE_NONE,
                CU_TENSOR_MAP_SWIZZLE_128B, CU_TENSOR_MAP_L2_PROMOTION_NONE, CU_TENSOR_MAP_FLOAT_OOB_FILL_NONE);
        }
        cudaFuncSetAttribute(attn_fwd_kernel, cudaFuncAttributeMaxDynamicSharedMemorySize, SMEM_BYTES);
        cached[0] = d_in[0]; cached[1] = d_in[1]; cached[2] = d_in[2]; cached[3] = d_out;
    }
    attn_fwd_kernel<<<2 * NUM_CLUSTERS, 384, SMEM_BYTES, cudaStreamPerThread>>>(tmQ, tmK, tmV, tmO, tmR, 0u, (const uint4*)d_in[0], (const uint4*)d_in[1],
                                                                                (const uint4*)d_in[2], (uint4*)d_out);
}
```

```cpp
#include <cuda_runtime.h>
#include <cuda_bf16.h>
#include <cuda.h>
#include <stdint.h>

namespace {

constexpr int NHEADS = 512;
constexpr int SQ = 848;
constexpr int SK = 512;
constexpr int DH = 192;
constexpr int ROW_BYTES = DH * 2;
constexpr int NBLK = SK / 64;
constexpr int NUM_CLUSTERS = 66;
constexpr int BIG_CLUSTERS = 17;

constexpr uint32_t GRP_BYTES = 3072, SLAB_BYTES = 1024;
constexpr uint32_t BLK_BYTES = 64 * ROW_BYTES;
constexpr uint32_t REM_BYTES = 16 * ROW_BYTES;
constexpr uint32_t SM_BASE = 1024;
constexpr uint32_t SM_BAR = 0;
constexpr uint32_t SM_REM = 1024;
constexpr uint32_t SM_V = SM_REM + REM_BYTES;
constexpr uint32_t SM_K = SM_V + 3 * BLK_BYTES;
constexpr uint32_t SM_QO = SM_K + 4 * BLK_BYTES;
constexpr uint32_t SM_PT = SM_QO + 2 * BLK_BYTES;
constexpr uint32_t SMEM_BYTES = SM_PT + 2 * 2048;
#define T_KVPF 4
#define KROT 2
constexpr uint32_t BAR_FULL = SM_BAR;
constexpr uint32_t BAR_DONE = BAR_FULL + 32;
constexpr uint32_t BAR_QFULL = BAR_DONE + 32;
constexpr uint32_t BAR_OREADY = BAR_QFULL + 16;
constexpr uint32_t BAR_STORED = BAR_OREADY + 16;
constexpr uint32_t BAR_DUMMY = BAR_STORED + 16;
constexpr uint32_t BAR_REMFREE = BAR_DUMMY + 8;
constexpr uint32_t BAR_SUMS = BAR_REMFREE + 8;
constexpr uint32_t SM_REDO = BAR_SUMS + 8;
static_assert(SMEM_BYTES <= 232448, "smem");

constexpr int PRODUCER_REGS = 24, CONSUMER_REGS = 240;
#define STAGE_SPLIT 4
#define STG_CVTK 7
#define STG_POS 0xBA987654
#define STG_N1 4
#define P6N 24
#define MS0 1
#define SK0 0
#define SDK 2
#define PUB_B 1
constexpr float SCALE_LOG2E = 0.07216878364870323f * 1.4426950408889634f;
constexpr uint32_t SCALE_HI = 0x3DD53DD5u, SCALE_LO = 0x38EE38EEu;
constexpr uint32_t SUM_LOW = (127u - 14u) << 23, SUM_HIGH = (127u + 32u) << 23;

const uint8_t START_TIME[NUM_CLUSTERS] = {167, 167, 167, 0, 0, 0, 185, 185, 185, 25, 25, 25, 42, 42, 42, 0, 0, 0, 96, 96, 96, 238, 238, 238, 60, 60, 60, 78, 78, 78, 131, 131, 131, 149, 149, 149, 0, 0, 0, 203, 203, 203, 7, 7, 7, 221, 221, 221, 114, 114, 114, 0, 88, 71, 176, 53, 106, 158, 193, 1, 141, 123, 18, 0, 0, 36};
constexpr int SCHED_COUNT = 29, SCHED_BREAKS = 30;
__constant__ __align__(8) uint16_t SCHED[NUM_CLUSTERS][36] = {
    {26624, 32868, 4280, 248, 16752, 6635, 468, 4688, 6783, 6860, 19228, 13148, 17172, 7195, 1104, 7292, 54436, 7511, 1420, 58796, 1588, 1624, 1724, 59128, 51028, 51048, 2036, 0, 0, 27, 256, 34818, 8224, 2048, 0, 167},
    {26625, 10341, 6329, 20729, 14705, 6563, 33237, 2641, 6807, 717, 15133, 13149, 6933, 43971, 7249, 7293, 1189, 7439, 1421, 1453, 58933, 58969, 59069, 59129, 51029, 3945, 2037, 0, 0, 27, 256, 34818, 8224, 2048, 0, 167},
    {26626, 12390, 186, 20730, 6514, 6619, 6614, 6738, 6727, 8910, 17182, 7006, 6934, 7171, 1106, 7294, 7334, 52543, 1422, 58798, 58934, 50778, 1726, 3834, 51030, 57194, 2038, 0, 0, 27, 256, 34818, 8224, 2048, 0, 167},
    {26628, 67, 6312, 204, 312, 57704, 444, 57879, 676, 688, 756, 2812, 768, 948, 992, 1192, 1256, 1320, 58736, 58820, 1560, 58964, 59016, 59136, 59180, 42868, 1992, 0, 0, 27, 128, 34816, 2, 2048, 0, 0},
    {26629, 75, 4265, 205, 57657, 361, 445, 551, 677, 2737, 757, 2813, 769, 949, 993, 1193, 1257, 58665, 58737, 1477, 58905, 1621, 1673, 1793, 59181, 59253, 1993, 0, 0, 27, 128, 34816, 2, 2048, 0, 0},
    {6, 3, 6314, 2254, 314, 362, 446, 57911, 678, 2738, 758, 766, 770, 950, 994, 1194, 1258, 1322, 1394, 1478, 58906, 1622, 59018, 59138, 59182, 51062, 1994, 0, 0, 27, 128, 34816, 2, 2048, 0, 0},
    {26632, 2144, 18708, 22828, 22900, 23032, 21012, 19032, 16972, 19112, 15184, 6916, 13264, 13396, 13420, 7371, 11412, 7503, 7572, 5547, 3592, 44647, 50840, 50908, 57116, 8108, 2016, 0, 0, 27, 0, 34850, 32768, 2056, 0, 185},
    {26633, 32865, 18709, 22829, 20853, 23033, 23061, 16985, 10829, 21161, 15185, 15109, 11217, 17493, 17517, 7323, 1173, 3399, 7573, 5611, 1545, 44623, 59033, 50909, 44829, 42925, 2017, 0, 0, 27, 0, 34850, 32768, 2056, 0, 185},
    {26634, 14434, 10518, 12590, 22902, 20986, 16918, 19034, 19022, 15018, 13138, 13062, 9170, 21590, 17518, 7411, 5270, 7463, 1430, 5579, 9738, 44615, 56986, 57054, 42782, 6062, 2018, 0, 0, 27, 0, 34850, 32768, 2056, 0, 185},
    {26636, 57403, 164, 2320, 49468, 4480, 8692, 480, 612, 748, 19116, 9048, 1004, 1060, 9332, 7412, 9392, 3396, 1423, 54728, 54796, 5708, 56988, 44752, 46916, 46992, 24512, 0, 0, 27, 0, 34820, 2, 2048, 0, 25},
    {20493, 57387, 2213, 49425, 49469, 2433, 2549, 481, 49765, 749, 4781, 2905, 7149, 7205, 9333, 5365, 7345, 1349, 42351, 5577, 1549, 46669, 46749, 46801, 10053, 46993, 24513, 0, 0, 27, 0, 34820, 2, 2048, 0, 25},
    {26638, 11, 166, 49426, 2366, 53634, 2550, 53730, 614, 8942, 686, 56154, 1006, 9254, 7286, 9462, 46258, 1350, 42343, 54730, 50702, 56910, 56990, 46802, 5958, 57234, 24514, 0, 0, 27, 0, 34820, 2, 2048, 0, 25},
    {18448, 112, 240, 41196, 344, 488, 464, 2600, 4732, 6883, 45784, 7056, 2972, 15364, 7280, 13516, 15572, 5412, 9600, 1516, 5616, 1592, 7864, 1892, 20300, 24428, 8183, 0, 0, 27, 0, 35840, 512, 2048, 0, 42},
    {26641, 49265, 41201, 2285, 345, 33257, 33233, 2601, 2685, 6859, 729, 5009, 5021, 15365, 46193, 46285, 7381, 1317, 7553, 9709, 7665, 1593, 1721, 22373, 24397, 24429, 8167, 0, 0, 27, 0, 35840, 512, 2048, 0, 42},
    {26642, 49266, 242, 41198, 346, 490, 466, 554, 8830, 6891, 2778, 13202, 45982, 15366, 15474, 7374, 7382, 1318, 1410, 1518, 7666, 3642, 5818, 3942, 24398, 65390, 8159, 0, 0, 27, 0, 35840, 512, 2048, 0, 42},
    {26644, 88, 172, 2316, 332, 2440, 12720, 4608, 2624, 4808, 13080, 45896, 2944, 13380, 13404, 7296, 11460, 3356, 3416, 34272, 9768, 3675, 57024, 14064, 5948, 57240, 24552, 0, 0, 27, 0, 2048, 0, 34848, 0, 0},
    {26645, 89, 173, 49421, 6477, 53641, 4529, 513, 2625, 56009, 793, 11081, 2945, 5189, 11357, 11393, 3269, 7453, 1369, 1505, 15913, 3667, 9921, 46833, 44861, 57241, 24553, 0, 0, 27, 0, 2048, 0, 34848, 0, 0},
    {26646, 90, 2222, 270, 51534, 2442, 2482, 41474, 578, 714, 56090, 2890, 45954, 7238, 7262, 11394, 13510, 3358, 1370, 5602, 3626, 1659, 3778, 7922, 46910, 57242, 24554, 0, 0, 27, 0, 2048, 0, 34848, 0, 0},
    {18456, 41052, 33024, 33020, 2340, 2504, 6548, 4692, 2712, 832, 875, 11124, 17404, 17472, 1120, 7295, 11480, 1304, 3484, 3547, 3604, 50812, 54964, 55048, 46880, 44964, 24572, 0, 0, 27, 32768, 2048, 1024, 34824, 0, 96},
    {24601, 41053, 33025, 253, 2341, 457, 6549, 597, 665, 2881, 795, 17269, 15357, 15425, 13409, 7343, 5337, 1305, 3485, 1459, 1557, 56957, 57013, 50953, 3873, 47013, 24573, 0, 0, 27, 32768, 2048, 1024, 34824, 0, 96},
    {14362, 41054, 33026, 33022, 33062, 2506, 406, 598, 6810, 834, 731, 17270, 9214, 13378, 7266, 7303, 13530, 3354, 1438, 44483, 56854, 56958, 57014, 46858, 42786, 47014, 24574, 0, 0, 27, 32768, 2048, 1024, 34824, 0, 96},
    {26652, 22708, 22724, 22824, 22880, 22936, 23088, 23152, 6731, 2884, 868, 988, 5048, 3124, 1084, 3208, 21740, 21780, 17756, 17852, 7719, 20096, 20204, 7883, 22312, 8055, 24516, 0, 0, 27, 0, 35344, 256, 2176, 0, 238},
    {26653, 22709, 22725, 22825, 22881, 22937, 18993, 14961, 6811, 837, 869, 989, 953, 1077, 3133, 1161, 21741, 21781, 15709, 9661, 7711, 16001, 20205, 7923, 24361, 8079, 24517, 0, 0, 27, 0, 35344, 256, 2176, 0, 238},
    {26654, 22710, 22726, 22826, 22882, 22938, 14898, 17010, 6755, 838, 870, 990, 3002, 3126, 11326, 13450, 23790, 17686, 21854, 11710, 7687, 24194, 24302, 7939, 1834, 8071, 24518, 0, 0, 27, 0, 35344, 256, 2176, 0, 238},
    {16416, 41088, 2208, 32992, 348, 33184, 4660, 6683, 4752, 744, 687, 828, 771, 960, 996, 1252, 1280, 1360, 58728, 1512, 1532, 50760, 1684, 1760, 50960, 44968, 1996, 0, 0, 27, 1024, 2048, 4224, 34816, 0, 60},
    {24609, 49281, 32929, 225, 33117, 417, 565, 2531, 4753, 6889, 807, 829, 50059, 961, 997, 1253, 1281, 58705, 1385, 1513, 58877, 1609, 59029, 1761, 59153, 42921, 1997, 0, 0, 27, 1024, 2048, 4224, 34816, 0, 60},
    {26658, 130, 162, 226, 33118, 418, 8758, 6699, 6802, 45802, 6903, 830, 987, 962, 998, 1254, 1282, 1362, 58730, 58858, 58878, 58954, 50838, 59106, 1810, 51114, 1998, 0, 0, 27, 1024, 2048, 4224, 34816, 0, 60},
    {26660, 132, 41123, 200, 4399, 57732, 6596, 4652, 49824, 720, 752, 824, 2948, 1024, 5091, 1248, 1284, 1324, 5512, 1484, 58872, 50788, 3728, 50940, 59160, 44948, 2012, 0, 0, 27, 16, 2048, 16388, 34816, 0, 78},
    {24613, 41093, 43155, 41161, 4407, 6533, 453, 49709, 673, 721, 753, 825, 901, 1025, 1107, 1249, 3333, 1325, 1417, 1485, 1529, 1637, 1681, 50941, 46873, 46997, 24541, 0, 0, 27, 16, 2048, 16388, 34816, 0, 78},
    {24614, 134, 41203, 202, 49471, 57734, 53702, 8750, 674, 722, 754, 826, 902, 50178, 939, 58594, 58630, 1326, 1418, 58830, 56826, 50790, 1682, 3838, 50970, 44950, 2014, 0, 0, 27, 16, 2048, 16388, 34816, 0, 78},
    {26664, 45180, 32988, 4404, 4520, 16892, 12808, 10884, 616, 17084, 3016, 2907, 11240, 5152, 5160, 5320, 3280, 3392, 11664, 5540, 11780, 22124, 7823, 1752, 3859, 57212, 24548, 0, 0, 27, 0, 2112, 2048, 35072, 0, 131},
    {26665, 41085, 2269, 2357, 12713, 14845, 14857, 8837, 4713, 8893, 7113, 6971, 11241, 9249, 9257, 1225, 5329, 5441, 17809, 17829, 15877, 20077, 7839, 1753, 1819, 3965, 24549, 0, 0, 27, 0, 2112, 2048, 35072, 0, 131},
    {26666, 6270, 4318, 2358, 6570, 20990, 23050, 17030, 2666, 8894, 3018, 5011, 13290, 7202, 5162, 3274, 1234, 5442, 13714, 7590, 9734, 20078, 7831, 24282, 3907, 57214, 24550, 0, 0, 27, 0, 2112, 2048, 35072, 0, 131},
    {26668, 45176, 45272, 18640, 10668, 12764, 21004, 2652, 14956, 19212, 852, 13220, 13268, 1036, 13400, 19708, 21820, 15632, 7515, 13728, 13892, 22148, 7879, 22368, 24372, 8091, 24560, 0, 0, 27, 0, 2112, 0, 35332, 0, 149},
    {26669, 32889, 217, 4305, 12717, 23005, 23053, 12893, 19053, 13069, 15189, 5029, 15317, 3085, 21593, 23805, 17725, 13585, 7555, 13729, 15941, 24197, 7855, 20321, 24373, 8043, 24561, 0, 0, 27, 0, 2112, 0, 35332, 0, 149},
    {26670, 32890, 218, 10450, 16814, 23006, 12814, 10846, 14958, 23310, 21334, 5030, 5078, 11278, 21594, 13566, 19774, 19730, 7547, 19874, 24134, 24198, 7871, 24418, 24374, 8115, 24562, 0, 0, 27, 0, 2112, 0, 35332, 0, 149},
    {26672, 83, 176, 280, 336, 57708, 57780, 2620, 652, 736, 876, 888, 784, 1052, 1044, 7340, 1272, 52532, 13720, 7600, 7668, 7800, 13992, 46796, 46920, 57220, 24504, 0, 0, 27, 0, 2048, 2, 34816, 0, 0},
    {26673, 51, 177, 281, 337, 57709, 57781, 57917, 653, 737, 877, 889, 785, 1053, 1045, 1197, 1273, 7477, 5529, 7601, 54773, 46713, 46761, 11981, 8009, 57221, 24505, 0, 0, 27, 0, 2048, 2, 34816, 0, 0},
    {26674, 19, 178, 2330, 338, 366, 438, 574, 654, 738, 878, 890, 786, 1054, 1046, 3246, 3322, 54582, 7578, 7602, 3574, 9850, 46762, 7886, 44874, 57222, 24506, 0, 0, 27, 0, 2048, 2, 34816, 0, 0},
    {26676, 22664, 22720, 22868, 22884, 20892, 21048, 17012, 16992, 19240, 17248, 19248, 5052, 5196, 7267, 1212, 1216, 21808, 24000, 15800, 7727, 7796, 16068, 18264, 8019, 57248, 8191, 0, 0, 27, 0, 35856, 16384, 2304, 0, 203},
    {26677, 22665, 22721, 20821, 22885, 22941, 21049, 19061, 21089, 19241, 21345, 15153, 11197, 17485, 7227, 1213, 23745, 21809, 13761, 23993, 7703, 3701, 9925, 24409, 7971, 57249, 8127, 0, 0, 27, 0, 35856, 16384, 2304, 0, 203},
    {26678, 16522, 22722, 22870, 22886, 22942, 23098, 19062, 21090, 19242, 17250, 19250, 15294, 7246, 7259, 1214, 1218, 11570, 15810, 13754, 7671, 1654, 11974, 24410, 7995, 57250, 8175, 0, 0, 27, 0, 35856, 16384, 2304, 0, 203},
    {26680, 116, 179, 57628, 57668, 57727, 440, 548, 668, 708, 804, 916, 908, 3056, 936, 1156, 1204, 54584, 11616, 1508, 3612, 3664, 1712, 46852, 12080, 46988, 24532, 0, 0, 27, 32, 34816, 4, 2048, 0, 7},
    {24633, 117, 155, 285, 325, 2407, 441, 549, 669, 709, 805, 917, 909, 1009, 937, 1157, 58549, 1337, 5473, 1509, 1565, 54865, 50865, 5893, 5937, 46989, 24533, 0, 0, 27, 32, 34816, 4, 2048, 0, 7},
    {26682, 49270, 171, 286, 326, 57711, 442, 550, 670, 710, 806, 918, 910, 1010, 938, 1158, 1206, 50490, 1378, 54758, 56862, 1618, 1714, 44806, 46898, 57230, 24534, 0, 0, 27, 32, 34816, 4, 2048, 0, 7},
    {26684, 22668, 18620, 6355, 288, 492, 33271, 540, 4728, 10980, 15208, 17264, 2835, 5144, 3088, 5276, 1191, 1288, 56700, 54708, 50704, 1600, 57004, 57044, 55096, 44956, 24536, 0, 0, 27, 64, 34817, 4104, 2048, 0, 221},
    {26685, 20621, 14525, 6395, 33057, 33261, 33223, 541, 6777, 10981, 11113, 13169, 2947, 3097, 1041, 5277, 7423, 5385, 50557, 52661, 50705, 1601, 57005, 50901, 44857, 44957, 2009, 0, 0, 27, 64, 34817, 4104, 2048, 0, 221},
    {26686, 32910, 22718, 6379, 33058, 33262, 33239, 542, 10874, 10982, 11114, 13170, 2971, 1050, 7186, 7326, 7431, 3338, 5502, 1462, 56850, 1602, 1710, 1750, 57146, 47006, 24538, 0, 0, 27, 64, 34817, 4104, 2048, 0, 221},
    {26688, 45160, 33028, 2280, 380, 460, 528, 10880, 584, 2744, 972, 7128, 1016, 3080, 1128, 21744, 5355, 15692, 13684, 3540, 9760, 5736, 12008, 20316, 8015, 65456, 8147, 0, 0, 27, 0, 2304, 0, 35841, 0, 114},
    {16449, 43113, 2309, 33001, 33149, 461, 12817, 4737, 2633, 697, 973, 985, 7161, 1033, 3177, 1265, 3251, 5453, 19829, 13781, 9761, 3689, 24297, 20317, 7991, 65457, 8131, 0, 0, 27, 0, 2304, 0, 35841, 0, 114},
    {10306, 106, 2310, 2282, 33150, 10702, 6674, 4738, 12874, 8890, 974, 9178, 1018, 5130, 5226, 5362, 7363, 7502, 9590, 7638, 11810, 7786, 16106, 18270, 7983, 65458, 8139, 0, 0, 27, 0, 2304, 0, 35841, 0, 114},
    {24644, 110, 41109, 265, 2371, 2444, 53648, 51716, 49807, 694, 811, 2893, 822, 1014, 1073, 1069, 1209, 1366, 1388, 1501, 58928, 1597, 59044, 1804, 59216, 59273, 2028, 0, 0, 27, 256, 2048, 1040, 34816, 0, 0},
    {26693, 32875, 41110, 2319, 8513, 8589, 6545, 2563, 660, 711, 814, 846, 819, 7156, 7247, 1082, 23692, 17630, 7475, 15748, 7655, 9730, 1628, 3763, 46837, 42855, 42864, 2040, 0, 28, 16904, 37392, 4226, 4228, 0, 88},
    {26694, 32876, 32916, 32982, 33059, 474, 41399, 517, 662, 691, 734, 844, 922, 1015, 1072, 1144, 1208, 1364, 58726, 58840, 58930, 58940, 59045, 59081, 50981, 59266, 1980, 0, 0, 27, 8256, 34816, 528, 2048, 0, 71},
    {26696, 22682, 6331, 33032, 330, 10712, 2455, 518, 6724, 11016, 8993, 6987, 921, 966, 1047, 1146, 1211, 1292, 1381, 58841, 1585, 58942, 59046, 1805, 1873, 59249, 2030, 0, 0, 27, 16448, 2048, 2052, 34817, 0, 176},
    {18505, 6253, 33027, 266, 335, 49550, 49595, 546, 631, 704, 2860, 892, 883, 15349, 7239, 3173, 3213, 5339, 7457, 7583, 1489, 5683, 54877, 50823, 1806, 1874, 59274, 2029, 0, 28, 16656, 37000, 4164, 4130, 0, 53},
    {26698, 43131, 33014, 41167, 306, 4516, 4594, 4632, 675, 726, 800, 767, 904, 947, 5037, 7279, 23704, 7379, 15650, 5495, 1449, 1547, 46688, 46732, 44783, 1856, 51065, 1973, 0, 28, 34824, 37128, 8450, 4130, 0, 106},
    {26700, 22681, 6363, 32980, 33119, 421, 497, 41497, 4677, 6867, 802, 2903, 905, 979, 942, 1071, 17568, 13582, 7524, 7644, 5539, 20005, 7791, 22246, 7931, 46869, 6015, 24530, 0, 28, 34832, 37952, 8708, 4368, 0, 158},
    {26701, 22680, 22773, 20693, 6571, 473, 6640, 16922, 582, 2825, 762, 2977, 2994, 1063, 9318, 7322, 1169, 11594, 11641, 15786, 13862, 15984, 24292, 7891, 24342, 8087, 24528, 0, 0, 27, 8192, 35328, 16, 2176, 0, 193},
    {24654, 49267, 156, 230, 49495, 378, 57803, 545, 2696, 705, 4829, 893, 820, 964, 1079, 3118, 5282, 1293, 3347, 13702, 7615, 24109, 7795, 1697, 24308, 24456, 8103, 24570, 0, 28, 16400, 37904, 66, 4164, 0, 1},
    {26704, 32907, 32926, 33055, 329, 2443, 4498, 57919, 649, 693, 835, 7038, 2869, 3007, 7084, 17464, 7307, 1244, 5407, 3448, 7634, 3630, 34363, 11936, 44815, 59172, 53106, 1982, 0, 28, 8328, 37124, 1058, 4161, 0, 141},
    {26705, 32867, 33012, 6375, 43336, 387, 449, 484, 607, 724, 699, 8952, 5002, 944, 7183, 11308, 19617, 7315, 13640, 7575, 3496, 1531, 7777, 46733, 42727, 51009, 42874, 1974, 0, 28, 16648, 37128, 1058, 4130, 0, 123},
    {18514, 41091, 41105, 279, 2353, 57715, 450, 527, 8842, 4715, 21258, 7119, 7072, 7147, 15432, 19556, 7399, 1168, 7467, 58733, 58846, 50688, 58978, 1678, 50888, 59202, 42872, 2001, 0, 28, 2184, 4097, 8738, 36868, 0, 18},
    {26708, 35, 146, 229, 2352, 422, 2559, 486, 643, 725, 6927, 21241, 7075, 945, 1097, 3191, 11417, 7314, 9545, 15738, 5584, 13860, 9842, 14053, 7899, 46868, 8111, 24500, 0, 28, 33856, 37888, 4354, 4352, 0, 0},
    {26709, 27, 144, 228, 57664, 49528, 2496, 485, 661, 692, 732, 2943, 920, 965, 1074, 7289, 1210, 1365, 7534, 5594, 3585, 54878, 46754, 46794, 46886, 34689, 24569, 0, 0, 27, 2048, 34816, 2, 2048, 0, 0},
    {24662, 41051, 157, 49351, 57666, 57721, 57755, 544, 599, 4802, 4909, 7011, 19362, 7167, 1098, 5177, 1166, 1245, 11552, 7557, 7635, 15916, 34417, 3751, 46838, 34651, 42880, 1981, 0, 28, 8456, 4224, 2114, 37392, 0, 36},
};
struct Starts { uint8_t of[52]; };

__device__ __forceinline__ uint32_t smem_u32(const void* p) { return (uint32_t)__cvta_generic_to_shared(p); }
__device__ __forceinline__ void mbar_init(uint32_t bar, uint32_t cnt) {
    asm volatile("mbarrier.init.shared::cta.b64 [%0], %1;" ::"r"(bar), "r"(cnt));
}
__device__ __forceinline__ void mbar_expect_tx(uint32_t bar, uint32_t bytes) {
    asm volatile("mbarrier.arrive.expect_tx.shared::cta.b64 _, [%0], %1;" ::"r"(bar), "r"(bytes) : "memory");
}
__device__ __forceinline__ void mbar_arrive(uint32_t bar) {
    asm volatile("mbarrier.arrive.shared::cta.b64 _, [%0];" ::"r"(bar) : "memory");
}
__device__ __forceinline__ void mbar_arrive_cluster_pred(uint32_t addr, uint32_t pred) {
    asm volatile(
        "{\n.reg .pred p;\n"
        "setp.ne.u32 p, %1, 0;\n"
        "@p mbarrier.arrive.shared::cluster.b64 _, [%0];\n}\n" ::"r"(addr), "r"(pred) : "memory");
}
__device__ __forceinline__ void mbar_arrive_pred(uint32_t addr, uint32_t pred) {
    asm volatile(
        "{\n.reg .pred p;\n"
        "setp.ne.u32 p, %1, 0;\n"
        "@p mbarrier.arrive.shared::cta.b64 _, [%0];\n}\n" ::"r"(addr), "r"(pred) : "memory");
}
__device__ __forceinline__ uint32_t mapa(uint32_t addr, uint32_t cta) {
    uint32_t r;
    asm("mapa.shared::cluster.u32 %0, %1, %2;" : "=r"(r) : "r"(addr), "r"(cta));
    return r;
}
__device__ __forceinline__ uint32_t cluster_rank() {
    uint32_t r;
    asm volatile("mov.u32 %0, %%cluster_ctarank;" : "=r"(r));
    return r;
}
__device__ __forceinline__ uint32_t cluster_size() {
    uint32_t r;
    asm volatile("mov.u32 %0, %%cluster_nctarank;" : "=r"(r));
    return r;
}
__device__ __forceinline__ void mbar_wait(uint32_t bar, uint32_t parity) {
    asm volatile(
        "{\n.reg .pred p;\n"
        "WAIT_LOOP:\n"
        "mbarrier.try_wait.parity.shared::cta.b64 p, [%0], %1;\n"
        "@p bra WAIT_DONE;\n"
        "bra WAIT_LOOP;\n"
        "WAIT_DONE:\n}\n" ::"r"(bar), "r"(parity) : "memory");
}
__device__ __forceinline__ void mbar_sleep(uint32_t bar, uint32_t parity) {
    asm volatile(
        "{\n.reg .pred p;\n"
        "WAIT_LOOP:\n"
        "mbarrier.try_wait.parity.shared::cta.b64 p, [%0], %1, 0x989680;\n"
        "@p bra WAIT_DONE;\n"
        "bra WAIT_LOOP;\n"
        "WAIT_DONE:\n}\n" ::"r"(bar), "r"(parity) : "memory");
}
__device__ __forceinline__ bool elect_one() {
    uint32_t pred;
    asm volatile("{\n.reg .pred p;\nelect.sync _|p, 0xffffffff;\nselp.u32 %0, 1, 0, p;\n}\n" : "=r"(pred));
    return pred != 0;
}
__device__ __forceinline__ void tma_load_kv(uint32_t dst, const CUtensorMap* tm, int g, uint32_t bar) {
    asm volatile(
        "cp.async.bulk.tensor.4d.shared::cluster.global.mbarrier::complete_tx::bytes [%0], [%1, {%3, %3, %3, %4}], [%2];" ::"r"(dst),
        "l"(tm), "r"(bar), "r"(0), "r"(g)
        : "memory");
}
__device__ __forceinline__ void tma_load_kv_mc(uint32_t dst, const CUtensorMap* tm, int g, uint32_t bar, uint16_t mask) {
    asm volatile(
        "cp.async.bulk.tensor.4d.shared::cluster.global.mbarrier::complete_tx::bytes.multicast::cluster [%0], [%1, {%3, %3, %3, %4}], [%2], %5;" ::"r"(dst),
        "l"(tm), "r"(bar), "r"(0), "r"(g), "h"(mask)
        : "memory");
}
__device__ __forceinline__ void tma_load_q(uint32_t dst, const CUtensorMap* tm, int g, int head, uint32_t bar) {
    asm volatile(
        "cp.async.bulk.tensor.5d.shared::cluster.global.mbarrier::complete_tx::bytes [%0], [%1, {%3, %3, %3, %4, %5}], [%2];" ::"r"(dst),
        "l"(tm), "r"(bar), "r"(0), "r"(g), "r"(head)
        : "memory");
}
__device__ __forceinline__ void tma_prefetch_q(const CUtensorMap* tm, int g, int head) {
    asm volatile("cp.async.bulk.prefetch.tensor.5d.L2.global [%0, {%1, %1, %1, %2, %3}];" ::"l"(tm), "r"(0), "r"(g), "r"(head) : "memory");
}
__device__ __forceinline__ void tma_store_o(const CUtensorMap* tm, uint32_t src, int g, int head) {
    asm volatile("cp.async.bulk.tensor.5d.global.shared::cta.bulk_group [%0, {%2, %2, %2, %3, %4}], [%1];" ::"l"(tm),
                 "r"(src), "r"(0), "r"(g), "r"(head)
                 : "memory");
}
__device__ __forceinline__ void bulk_commit() { asm volatile("cp.async.bulk.commit_group;" ::: "memory"); }
__device__ __forceinline__ void bulk_wait_read() { asm volatile("cp.async.bulk.wait_group.read 0;" ::: "memory"); }
__device__ __forceinline__ void fence_async_smem() { asm volatile("fence.proxy.async.shared::cta;" ::: "memory"); }
__device__ __forceinline__ void stsm_x4(uint32_t addr, uint32_t r0, uint32_t r1, uint32_t r2, uint32_t r3) {
    asm volatile("stmatrix.sync.aligned.m8n8.x4.shared.b16 [%0], {%1, %2, %3, %4};" ::"r"(addr), "r"(r0), "r"(r1), "r"(r2), "r"(r3) : "memory");
}
__device__ __forceinline__ void ldsm_x4(uint32_t addr, uint32_t& r0, uint32_t& r1, uint32_t& r2, uint32_t& r3) {
    asm volatile("ldmatrix.sync.aligned.m8n8.x4.shared.b16 {%0, %1, %2, %3}, [%4];" : "=r"(r0), "=r"(r1), "=r"(r2), "=r"(r3) : "r"(addr) : "memory");
}
__device__ __forceinline__ void wgmma_fence() { asm volatile("wgmma.fence.sync.aligned;" ::: "memory"); }
__device__ __forceinline__ void wgmma_commit() { asm volatile("wgmma.commit_group.sync.aligned;" ::: "memory"); }
template <int N>
__device__ __forceinline__ void wgmma_wait() { asm volatile("wgmma.wait_group.sync.aligned %0;" ::"n"(N) : "memory"); }
__device__ __forceinline__ void bar_sync(int id, int n) { asm volatile("bar.sync %0, %1;" ::"r"(id), "r"(n) : "memory"); }
__device__ __forceinline__ void bar_arrive(int id, int n) { asm volatile("bar.arrive %0, %1;" ::"r"(id), "r"(n) : "memory"); }
__device__ __forceinline__ float ex2(float x) {
    float y;
    asm("ex2.approx.ftz.f32 %0, %1;" : "=f"(y) : "f"(x));
    return y;
}
__device__ __forceinline__ uint32_t pack_bf16(float lo, float hi) {
    uint32_t r;
    asm("cvt.rn.bf16x2.f32 %0, %1, %2;" : "=r"(r) : "f"(hi), "f"(lo));
    return r;
}
template <int N>
__device__ __forceinline__ void fence_regs(float (&r)[N]) {
#pragma unroll
    for (int i = 0; i < N; i++) asm volatile("" : "+f"(r[i])::"memory");
}
template <int N>
__device__ __forceinline__ void fence_regs(uint32_t (&r)[N]) {
#pragma unroll
    for (int i = 0; i < N; i++) asm volatile("" : "+r"(r[i])::"memory");
}
template <int N>
__device__ __forceinline__ void forget(float (&r)[N]) {
#pragma unroll
    for (int i = 0; i < N; i++) r[i] = 0.f;
}
__device__ __forceinline__ uint64_t make_desc(uint32_t lo, uint32_t hi) { return ((uint64_t)hi << 32) | lo; }
constexpr uint32_t DESC_HI = (GRP_BYTES >> 4) | (1u << 30);

__device__ __forceinline__ void wgmma_qk(float (&d)[32], uint32_t a0, uint32_t a1, uint32_t a2, uint32_t a3, uint64_t descB) {
    asm volatile(
        "{\n.reg .pred p;\n"
        "setp.eq.b32 p, 0, 0;\n"
        "wgmma.mma_async.sync.aligned.m64n64k16.f32.bf16.bf16 "
        "{%0, %1, %2, %3, %4, %5, %6, %7, %8, %9, %10, %11, %12, %13, %14, %15, "
        "%16, %17, %18, %19, %20, %21, %22, %23, %24, %25, %26, %27, %28, %29, %30, %31}, "
        "{%32, %33, %34, %35}, %36, p, 1, 1, 0;\n}\n"
        : "+f"(d[0]), "+f"(d[1]), "+f"(d[2]), "+f"(d[3]), "+f"(d[4]), "+f"(d[5]), "+f"(d[6]), "+f"(d[7]),
          "+f"(d[8]), "+f"(d[9]), "+f"(d[10]), "+f"(d[11]), "+f"(d[12]), "+f"(d[13]), "+f"(d[14]), "+f"(d[15]),
          "+f"(d[16]), "+f"(d[17]), "+f"(d[18]), "+f"(d[19]), "+f"(d[20]), "+f"(d[21]), "+f"(d[22]), "+f"(d[23]),
          "+f"(d[24]), "+f"(d[25]), "+f"(d[26]), "+f"(d[27]), "+f"(d[28]), "+f"(d[29]), "+f"(d[30]), "+f"(d[31])
        : "r"(a0), "r"(a1), "r"(a2), "r"(a3), "l"(descB));
}

__device__ __forceinline__ void wgmma_qk_init(float (&d)[32], uint32_t a0, uint32_t a1, uint32_t a2, uint32_t a3, uint64_t descB) {
    asm volatile(
        "{\n.reg .pred p;\n"
        "setp.ne.b32 p, 0, 0;\n"
        "wgmma.mma_async.sync.aligned.m64n64k16.f32.bf16.bf16 "
        "{%0, %1, %2, %3, %4, %5, %6, %7, %8, %9, %10, %11, %12, %13, %14, %15, "
        "%16, %17, %18, %19, %20, %21, %22, %23, %24, %25, %26, %27, %28, %29, %30, %31}, "
        "{%32, %33, %34, %35}, %36, p, 1, 1, 0;\n}\n"
        : "=f"(d[0]), "=f"(d[1]), "=f"(d[2]), "=f"(d[3]), "=f"(d[4]), "=f"(d[5]), "=f"(d[6]), "=f"(d[7]),
          "=f"(d[8]), "=f"(d[9]), "=f"(d[10]), "=f"(d[11]), "=f"(d[12]), "=f"(d[13]), "=f"(d[14]), "=f"(d[15]),
          "=f"(d[16]), "=f"(d[17]), "=f"(d[18]), "=f"(d[19]), "=f"(d[20]), "=f"(d[21]), "=f"(d[22]), "=f"(d[23]),
          "=f"(d[24]), "=f"(d[25]), "=f"(d[26]), "=f"(d[27]), "=f"(d[28]), "=f"(d[29]), "=f"(d[30]), "=f"(d[31])
        : "r"(a0), "r"(a1), "r"(a2), "r"(a3), "l"(descB));
}

__device__ __forceinline__ void wgmma_pv(float (&d)[96], uint32_t a0, uint32_t a1, uint32_t a2, uint32_t a3, uint64_t descB) {
    asm volatile(
        "{\n.reg .pred p;\n"
        "setp.eq.b32 p, 0, 0;\n"
        "wgmma.mma_async.sync.aligned.m64n192k16.f32.bf16.bf16 "
        "{%0, %1, %2, %3, %4, %5, %6, %7, %8, %9, %10, %11, %12, %13, %14, %15, "
        "%16, %17, %18, %19, %20, %21, %22, %23, %24, %25, %26, %27, %28, %29, %30, %31, "
        "%32, %33, %34, %35, %36, %37, %38, %39, %40, %41, %42, %43, %44, %45, %46, %47, "
        "%48, %49, %50, %51, %52, %53, %54, %55, %56, %57, %58, %59, %60, %61, %62, %63, "
        "%64, %65, %66, %67, %68, %69, %70, %71, %72, %73, %74, %75, %76, %77, %78, %79, "
        "%80, %81, %82, %83, %84, %85, %86, %87, %88, %89, %90, %91, %92, %93, %94, %95}, "
        "{%96, %97, %98, %99}, %100, p, 1, 1, 1;\n}\n"
        : "+f"(d[0]), "+f"(d[1]), "+f"(d[2]), "+f"(d[3]), "+f"(d[4]), "+f"(d[5]), "+f"(d[6]), "+f"(d[7]),
          "+f"(d[8]), "+f"(d[9]), "+f"(d[10]), "+f"(d[11]), "+f"(d[12]), "+f"(d[13]), "+f"(d[14]), "+f"(d[15]),
          "+f"(d[16]), "+f"(d[17]), "+f"(d[18]), "+f"(d[19]), "+f"(d[20]), "+f"(d[21]), "+f"(d[22]), "+f"(d[23]),
          "+f"(d[24]), "+f"(d[25]), "+f"(d[26]), "+f"(d[27]), "+f"(d[28]), "+f"(d[29]), "+f"(d[30]), "+f"(d[31]),
          "+f"(d[32]), "+f"(d[33]), "+f"(d[34]), "+f"(d[35]), "+f"(d[36]), "+f"(d[37]), "+f"(d[38]), "+f"(d[39]),
          "+f"(d[40]), "+f"(d[41]), "+f"(d[42]), "+f"(d[43]), "+f"(d[44]), "+f"(d[45]), "+f"(d[46]), "+f"(d[47]),
          "+f"(d[48]), "+f"(d[49]), "+f"(d[50]), "+f"(d[51]), "+f"(d[52]), "+f"(d[53]), "+f"(d[54]), "+f"(d[55]),
          "+f"(d[56]), "+f"(d[57]), "+f"(d[58]), "+f"(d[59]), "+f"(d[60]), "+f"(d[61]), "+f"(d[62]), "+f"(d[63]),
          "+f"(d[64]), "+f"(d[65]), "+f"(d[66]), "+f"(d[67]), "+f"(d[68]), "+f"(d[69]), "+f"(d[70]), "+f"(d[71]),
          "+f"(d[72]), "+f"(d[73]), "+f"(d[74]), "+f"(d[75]), "+f"(d[76]), "+f"(d[77]), "+f"(d[78]), "+f"(d[79]),
          "+f"(d[80]), "+f"(d[81]), "+f"(d[82]), "+f"(d[83]), "+f"(d[84]), "+f"(d[85]), "+f"(d[86]), "+f"(d[87]),
          "+f"(d[88]), "+f"(d[89]), "+f"(d[90]), "+f"(d[91]), "+f"(d[92]), "+f"(d[93]), "+f"(d[94]), "+f"(d[95])
        : "r"(a0), "r"(a1), "r"(a2), "r"(a3), "l"(descB));
}

__device__ __forceinline__ void wgmma_pv_init(float (&d)[96], uint32_t a0, uint32_t a1, uint32_t a2, uint32_t a3, uint64_t descB) {
    asm volatile(
        "{\n.reg .pred p;\n"
        "setp.ne.b32 p, 0, 0;\n"
        "wgmma.mma_async.sync.aligned.m64n192k16.f32.bf16.bf16 "
        "{%0, %1, %2, %3, %4, %5, %6, %7, %8, %9, %10, %11, %12, %13, %14, %15, "
        "%16, %17, %18, %19, %20, %21, %22, %23, %24, %25, %26, %27, %28, %29, %30, %31, "
        "%32, %33, %34, %35, %36, %37, %38, %39, %40, %41, %42, %43, %44, %45, %46, %47, "
        "%48, %49, %50, %51, %52, %53, %54, %55, %56, %57, %58, %59, %60, %61, %62, %63, "
        "%64, %65, %66, %67, %68, %69, %70, %71, %72, %73, %74, %75, %76, %77, %78, %79, "
        "%80, %81, %82, %83, %84, %85, %86, %87, %88, %89, %90, %91, %92, %93, %94, %95}, "
        "{%96, %97, %98, %99}, %100, p, 1, 1, 1;\n}\n"
        : "=f"(d[0]), "=f"(d[1]), "=f"(d[2]), "=f"(d[3]), "=f"(d[4]), "=f"(d[5]), "=f"(d[6]), "=f"(d[7]),
          "=f"(d[8]), "=f"(d[9]), "=f"(d[10]), "=f"(d[11]), "=f"(d[12]), "=f"(d[13]), "=f"(d[14]), "=f"(d[15]),
          "=f"(d[16]), "=f"(d[17]), "=f"(d[18]), "=f"(d[19]), "=f"(d[20]), "=f"(d[21]), "=f"(d[22]), "=f"(d[23]),
          "=f"(d[24]), "=f"(d[25]), "=f"(d[26]), "=f"(d[27]), "=f"(d[28]), "=f"(d[29]), "=f"(d[30]), "=f"(d[31]),
          "=f"(d[32]), "=f"(d[33]), "=f"(d[34]), "=f"(d[35]), "=f"(d[36]), "=f"(d[37]), "=f"(d[38]), "=f"(d[39]),
          "=f"(d[40]), "=f"(d[41]), "=f"(d[42]), "=f"(d[43]), "=f"(d[44]), "=f"(d[45]), "=f"(d[46]), "=f"(d[47]),
          "=f"(d[48]), "=f"(d[49]), "=f"(d[50]), "=f"(d[51]), "=f"(d[52]), "=f"(d[53]), "=f"(d[54]), "=f"(d[55]),
          "=f"(d[56]), "=f"(d[57]), "=f"(d[58]), "=f"(d[59]), "=f"(d[60]), "=f"(d[61]), "=f"(d[62]), "=f"(d[63]),
          "=f"(d[64]), "=f"(d[65]), "=f"(d[66]), "=f"(d[67]), "=f"(d[68]), "=f"(d[69]), "=f"(d[70]), "=f"(d[71]),
          "=f"(d[72]), "=f"(d[73]), "=f"(d[74]), "=f"(d[75]), "=f"(d[76]), "=f"(d[77]), "=f"(d[78]), "=f"(d[79]),
          "=f"(d[80]), "=f"(d[81]), "=f"(d[82]), "=f"(d[83]), "=f"(d[84]), "=f"(d[85]), "=f"(d[86]), "=f"(d[87]),
          "=f"(d[88]), "=f"(d[89]), "=f"(d[90]), "=f"(d[91]), "=f"(d[92]), "=f"(d[93]), "=f"(d[94]), "=f"(d[95])
        : "r"(a0), "r"(a1), "r"(a2), "r"(a3), "l"(descB));
}

__device__ __forceinline__ void wgmma_rk(float (&d)[8], uint64_t descA, uint64_t descB) {
    asm volatile(
        "{\n.reg .pred p;\n"
        "setp.eq.b32 p, 0, 0;\n"
        "wgmma.mma_async.sync.aligned.m64n16k16.f32.bf16.bf16 "
        "{%0, %1, %2, %3, %4, %5, %6, %7}, "
        "%8, %9, p, 1, 1, 0, 0;\n}\n"
        : "+f"(d[0]), "+f"(d[1]), "+f"(d[2]), "+f"(d[3]), "+f"(d[4]), "+f"(d[5]), "+f"(d[6]), "+f"(d[7])
        : "l"(descA), "l"(descB));
}

__device__ __forceinline__ void wgmma_rk_init(float (&d)[8], uint64_t descA, uint64_t descB) {
    asm volatile(
        "{\n.reg .pred p;\n"
        "setp.ne.b32 p, 0, 0;\n"
        "wgmma.mma_async.sync.aligned.m64n16k16.f32.bf16.bf16 "
        "{%0, %1, %2, %3, %4, %5, %6, %7}, "
        "%8, %9, p, 1, 1, 0, 0;\n}\n"
        : "=f"(d[0]), "=f"(d[1]), "=f"(d[2]), "=f"(d[3]), "=f"(d[4]), "=f"(d[5]), "=f"(d[6]), "=f"(d[7])
        : "l"(descA), "l"(descB));
}

__device__ __forceinline__ void wgmma_rv(float (&d)[8], uint64_t descA, uint64_t descB) {
    asm volatile(
        "{\n.reg .pred p;\n"
        "setp.eq.b32 p, 0, 0;\n"
        "wgmma.mma_async.sync.aligned.m64n16k16.f32.bf16.bf16 "
        "{%0, %1, %2, %3, %4, %5, %6, %7}, "
        "%8, %9, p, 1, 1, 1, 0;\n}\n"
        : "+f"(d[0]), "+f"(d[1]), "+f"(d[2]), "+f"(d[3]), "+f"(d[4]), "+f"(d[5]), "+f"(d[6]), "+f"(d[7])
        : "l"(descA), "l"(descB));
}

__device__ __forceinline__ void wgmma_rl(float (&d)[8], uint32_t a0, uint32_t a1, uint32_t a2, uint32_t a3, uint64_t descB) {
    asm volatile(
        "{\n.reg .pred p;\n"
        "setp.eq.b32 p, 0, 0;\n"
        "wgmma.mma_async.sync.aligned.m64n16k16.f32.bf16.bf16 "
        "{%0, %1, %2, %3, %4, %5, %6, %7}, "
        "{%8, %9, %10, %11}, %12, p, 1, 1, 0;\n}\n"
        : "+f"(d[0]), "+f"(d[1]), "+f"(d[2]), "+f"(d[3]), "+f"(d[4]), "+f"(d[5]), "+f"(d[6]), "+f"(d[7])
        : "r"(a0), "r"(a1), "r"(a2), "r"(a3), "l"(descB));
}

__device__ __forceinline__ void wgmma_rl_init(float (&d)[8], uint32_t a0, uint32_t a1, uint32_t a2, uint32_t a3, uint64_t descB) {
    asm volatile(
        "{\n.reg .pred p;\n"
        "setp.ne.b32 p, 0, 0;\n"
        "wgmma.mma_async.sync.aligned.m64n16k16.f32.bf16.bf16 "
        "{%0, %1, %2, %3, %4, %5, %6, %7}, "
        "{%8, %9, %10, %11}, %12, p, 1, 1, 0;\n}\n"
        : "=f"(d[0]), "=f"(d[1]), "=f"(d[2]), "=f"(d[3]), "=f"(d[4]), "=f"(d[5]), "=f"(d[6]), "=f"(d[7])
        : "r"(a0), "r"(a1), "r"(a2), "r"(a3), "l"(descB));
}


struct Item { int head; int grp; bool mc, rem; };
__device__ __forceinline__ Item decode_item(uint32_t e, int rank, int w) {
    Item it;
    e &= 0x7FF;
    it.mc = (e & 3) != 3;
    it.rem = !it.mc && (e >> 2 & 1) != w;
    it.head = it.mc ? e >> 2 : (e >> 3) * 2 + rank;
    it.grp = 32 * (e & 3) + (it.mc ? 16 * rank + 8 * w : it.rem ? 8 : 0);
    return it;
}
__device__ __forceinline__ uint32_t first_entry(uint32_t c) { return (c / 3) * 4 + c % 3; }

__device__ __forceinline__ uint32_t k_addr(int e) { return SM_K + ((e + KROT) & 3) * BLK_BYTES; }
__device__ __forceinline__ void next_v(uint32_t& v) { v = v == SM_V + 2 * BLK_BYTES ? SM_V : v + BLK_BYTES; }
__device__ __forceinline__ void wait_blocks(uint32_t sbase, int e) { mbar_wait(sbase + BAR_FULL + 8 * (e & 3), e >> 2 & 1); }
__device__ __forceinline__ uint64_t k_desc(int e) {
    return make_desc(((e + KROT) & 3) * (BLK_BYTES >> 4) + (((SM_BASE + SM_K) >> 4) | (1u << 16)), DESC_HI);
}
constexpr uint32_t V_DESC0 = ((SM_BASE + SM_V) >> 4) | ((SLAB_BYTES >> 4) << 16);
__device__ __forceinline__ void next_v_desc(uint32_t& v) { v = v == V_DESC0 + 2 * (BLK_BYTES >> 4) ? V_DESC0 : v + (BLK_BYTES >> 4); }
__device__ __forceinline__ constexpr uint32_t k_step(int k) { return (k & 3) == 3 ? (SLAB_BYTES >> 4) - 6 : 2; }

template <bool SPLIT>
__device__ __forceinline__ void issue_qk(float (&s)[32], uint32_t (&q)[48], int e) {
    fence_regs(q);
    wgmma_fence();
    uint64_t desc = k_desc(e);
#pragma unroll
    for (int k = 0; k < 12; k++) {
        if (k == 0) wgmma_qk_init(s, q[0], q[1], q[2], q[3], desc);
        else wgmma_qk(s, q[4 * k], q[4 * k + 1], q[4 * k + 2], q[4 * k + 3], desc);
        if (k < 11) desc += k_step(k);
        if (SPLIT && (k & 3) == 3) wgmma_commit();
    }
    if (!SPLIT) wgmma_commit();
}
template <bool FIRST, bool WAIT = true, bool FENCE = true>
__device__ __forceinline__ void issue_pv(float (&o)[96], uint32_t (&p)[16], uint32_t sbase, int b, uint32_t& v) {
    if (WAIT) wait_blocks(sbase, b + 2);
    if (!FIRST) fence_regs(o);
    fence_regs(p);
    if (FENCE) wgmma_fence();
    uint64_t desc = make_desc(v, DESC_HI);
#pragma unroll
    for (int k = 0; k < 4; k++) {
        if (FIRST && k == 0) wgmma_pv_init(o, p[0], p[1], p[2], p[3], desc);
        else wgmma_pv(o, p[4 * k], p[4 * k + 1], p[4 * k + 2], p[4 * k + 3], desc);
        if (k < 3) desc += 2 * GRP_BYTES >> 4;
    }
    wgmma_commit();
    next_v_desc(v);
}

__device__ __forceinline__ float opaque_copy(float x, uint32_t zero) { return x + __uint_as_float(zero); }

__device__ __forceinline__ float after(float x, float y, uint32_t zero) { return __uint_as_float(__float_as_uint(x) | (__float_as_uint(y) & zero)); }

template <bool FIRST>
__device__ __forceinline__ void exp_sum(float (&s)[32], float (&l)[2]) {
#pragma unroll
    for (int i = 0; i < 32; i++) s[i] = ex2(s[i]);
#pragma unroll
    for (int i = 0; i < 8; i++) {
        const float x = s[4 * i] + s[4 * i + 1], y = s[4 * i + 2] + s[4 * i + 3];
        if (FIRST && i == 0) { l[0] = x; l[1] = y; }
        else { l[0] += x; l[1] += y; }
    }
}
template <int LO, int HI>
__device__ __forceinline__ void exp_only(float (&s)[32]) {
#pragma unroll
    for (int i = LO; i < HI; i++) s[i] = ex2(s[i]);
}
__device__ __forceinline__ void sum_only(const float (&s)[32], float (&l)[2]) {
#pragma unroll
    for (int i = 0; i < 8; i++) { l[0] += s[4 * i] + s[4 * i + 1]; l[1] += s[4 * i + 2] + s[4 * i + 3]; }
}
__device__ __forceinline__ void pack_p(const float (&s)[32], uint32_t (&p)[16]) {
#pragma unroll
    for (int i = 0; i < 8; i++) {
        p[2 * i] = pack_bf16(s[4 * i], s[4 * i + 1]);
        p[2 * i + 1] = pack_bf16(s[4 * i + 2], s[4 * i + 3]);
    }
}
__device__ __forceinline__ bool sum_unsafe(float l) { return __float_as_uint(l) - SUM_LOW > SUM_HIGH - SUM_LOW; }

__device__ __forceinline__ void bb_boundary(uint32_t zero, float& x, float& y) {
    if (zero) {
#pragma unroll
        for (int i = 0; i < 12; i++) {
            asm volatile("mul.f32 %0, %0, %1;" : "+f"(x) : "f"(y));
            asm volatile("mul.f32 %0, %0, %1;" : "+f"(y) : "f"(x));
        }
    }
}
__device__ __forceinline__ void bb_boundary(uint32_t zero, float (&x)[2][2]) {
    if (zero) {
#pragma unroll
        for (int i = 0; i < 24; i++) asm volatile("mul.f32 %0, %0, %1;" : "+f"(x[i >> 1 & 1][i & 1]) : "f"(x[~i >> 1 & 1][i & 1]));
    }
}
__device__ __forceinline__ void bb_boundary(uint32_t zero, float (&x)[4]) {
    if (zero) {
#pragma unroll
        for (int i = 0; i < 24; i++) asm volatile("mul.f32 %0, %0, %1;" : "+f"(x[i & 3]) : "f"(x[(i + 2) & 3]));
    }
}
__device__ __forceinline__ uint32_t sched_fence() {
    uint32_t c;
    asm volatile("mov.u32 %0, %%clock;" : "=r"(c)::"memory");
    return c;
}
template <int CB>
__device__ __forceinline__ void load_q_slab(uint32_t (&q)[48], const uint32_t (&q_lane)[4]) {
#pragma unroll
    for (int k = 4 * CB; k < 4 * CB + 4; k++)
        ldsm_x4(q_lane[k & 3] + CB * SLAB_BYTES, q[4 * k], q[4 * k + 1], q[4 * k + 2], q[4 * k + 3]);
}
template <int LO, int HI, int STEP = 1>
__device__ __forceinline__ void scale_q(uint32_t (&q)[48]) {
#pragma unroll
    for (int i = LO; i < HI; i += STEP)
        asm("{\n.reg .b32 t;\nmul.rn.bf16x2 t, %0, %1;\nfma.rn.bf16x2 %0, %0, %2, t;\n}\n" : "+r"(q[i]) : "r"(SCALE_LO), "r"(SCALE_HI));
}
__device__ __forceinline__ void row_normalisers(float l0, float l1, float (&inv)[2][2], uint32_t& redo, uint32_t bit, uint32_t zero) {
    l0 += __shfl_xor_sync(0xffffffffu, l0, 1);
    l1 += __shfl_xor_sync(0xffffffffu, l1, 1);
    l0 += __shfl_xor_sync(0xffffffffu, l0, 2);
    l1 += __shfl_xor_sync(0xffffffffu, l1, 2);
    asm("rcp.approx.ftz.f32 %0, %1;" : "=f"(inv[0][0]) : "f"(l0));
    asm("rcp.approx.ftz.f32 %0, %1;" : "=f"(inv[1][0]) : "f"(l1));
    inv[0][1] = opaque_copy(inv[0][0], zero);
    inv[1][1] = opaque_copy(inv[1][0], zero);
    if (sum_unsafe(l0) | sum_unsafe(l1)) redo |= bit;
}
__device__ __forceinline__ void cvt_out(float (&o)[96], int k, const float (&inv)[2][2], uint32_t (&x)[4]) {
    float y[8];
#pragma unroll
    for (int i = 0; i < 8; i++) y[i] = o[8 * k + i] * inv[i >> 1 & 1][i & 1];
#pragma unroll
    for (int i = 0; i < 4; i++) x[i] = pack_bf16(y[2 * i], y[2 * i + 1]);
}
template <int K0, int K1, bool GAPS>
__device__ __forceinline__ void stage_output(float (&o)[96], const float (&inv)[2][2], const uint32_t (&q_lane)[4]) {
#pragma unroll
    for (int k = K0; k < K1; k++) {
        uint32_t x[4];
        cvt_out(o, k, inv, x);
        if (GAPS) wgmma_wait<0>();
        stsm_x4(q_lane[k & 3] + (k >> 2) * SLAB_BYTES, x[0], x[1], x[2], x[3]);
    }
}
template <int K0>
__device__ __forceinline__ void issue_qk_stage(float (&s)[32], uint32_t (&q)[48], int e, float (&o)[96], float (&inv)[2][2], const uint32_t (&q_lane)[4],
                                               uint32_t& keep) {
    constexpr int NS = 12 - K0;
    uint32_t x[NS][4];
#pragma unroll
    for (int j = 0; j < STG_N1; j++) cvt_out(o, K0 + j, inv, x[j]);
    fence_regs(q);
    wgmma_fence();
    uint64_t desc = k_desc(e);
#pragma unroll
    for (int k = 0; k < 12; k++) {
        if (k == 0) wgmma_qk_init(s, q[0], q[1], q[2], q[3], desc);
        else wgmma_qk(s, q[4 * k], q[4 * k + 1], q[4 * k + 2], q[4 * k + 3], desc);
        if (k < 11) desc += k_step(k);
        if (k == STG_CVTK) {
            keep &= sched_fence();
            fence_regs(inv[0]); fence_regs(inv[1]);
#pragma unroll
            for (int j = STG_N1; j < NS; j++) cvt_out(o, K0 + j, inv, x[j]);
        }
#pragma unroll
        for (int j = 0; j < NS; j++)
            if (k == (STG_POS >> 4 * j & 15)) stsm_x4(q_lane[(K0 + j) & 3] + ((K0 + j) >> 2) * SLAB_BYTES, x[j][0], x[j][1], x[j][2], x[j][3]);
    }
    wgmma_commit();
}
__device__ __forceinline__ void publish_output(uint32_t oready, int lane) {
    fence_async_smem();
    __syncwarp();
    mbar_arrive_pred(oready, lane == 0);
}

__device__ __forceinline__ void stsm_x4_t(uint32_t addr, uint32_t r0, uint32_t r1, uint32_t r2, uint32_t r3) {
    asm volatile("stmatrix.sync.aligned.m8n8.x4.trans.shared.b16 [%0], {%1, %2, %3, %4};" ::"r"(addr), "r"(r0), "r"(r1), "r"(r2), "r"(r3) : "memory");
}
__device__ __forceinline__ void issue_rem_qk(float (&s)[8], int e) {
    uint64_t da = k_desc(e), db = make_desc(((SM_BASE + SM_REM) >> 4) | (1u << 16), DESC_HI);
#pragma unroll
    for (int k = 0; k < 12; k++) {
        if (k == 0) wgmma_rk_init(s, da, db);
        else wgmma_rk(s, da, db);
        if (k < 11) { da += k_step(k); db += k_step(k); }
    }
    wgmma_commit();
}
constexpr uint32_t PT_DESC_HI = (1024 >> 4) | (1u << 30);
__device__ __forceinline__ void issue_rem_pv(float (&o)[3][8], uint32_t pt, uint32_t& v) {
    const uint64_t da = make_desc(v, DESC_HI), db = make_desc(pt * (2048 >> 4) + (((SM_BASE + SM_PT) >> 4) | (1u << 16)), PT_DESC_HI);
#pragma unroll
    for (int k = 0; k < 4; k++)
#pragma unroll
        for (int m = 0; m < 3; m++) wgmma_rv(o[m], da + k * (2 * GRP_BYTES >> 4) + m * (SLAB_BYTES >> 4), db + 2 * k);
    wgmma_commit();
    next_v_desc(v);
}
__device__ __forceinline__ void rem_softmax(float (&s)[8], float (&l)[4]) {
#pragma unroll
    for (int i = 0; i < 8; i++) s[i] = ex2(s[i] * SCALE_LOG2E);
    l[0] += s[0] + s[2]; l[1] += s[1] + s[3]; l[2] += s[4] + s[6]; l[3] += s[5] + s[7];
}
__device__ __forceinline__ void rem_store(const float (&s)[8], uint32_t addr) {
    stsm_x4_t(addr, pack_bf16(s[0], s[1]), pack_bf16(s[2], s[3]), pack_bf16(s[4], s[5]), pack_bf16(s[6], s[7]));
}

__device__ __forceinline__ void mma_16816(float (&c)[4], uint32_t a0, uint32_t a1, uint32_t a2, uint32_t a3, uint32_t b0, uint32_t b1) {
    asm volatile("mma.sync.aligned.m16n8k16.row.col.f32.bf16.bf16.f32 {%0, %1, %2, %3}, {%4, %5, %6, %7}, {%8, %9}, {%0, %1, %2, %3};"
                 : "+f"(c[0]), "+f"(c[1]), "+f"(c[2]), "+f"(c[3]) : "r"(a0), "r"(a1), "r"(a2), "r"(a3), "r"(b0), "r"(b1));
}
__device__ __forceinline__ void exact_rows(const uint4* __restrict__ gq, const uint4* __restrict__ gk, const uint4* __restrict__ gv, uint4* __restrict__ go,
                                           int head, int row0, int lane) {
    constexpr int R = ROW_BYTES / 16;
    const int g = lane >> 2, c = lane & 3;
    const uint4* pq = gq + ((size_t)head * SQ + row0 + g) * R + c;
    uint4 qa[6], qb[6];
#pragma unroll
    for (int k = 0; k < 6; k++) { qa[k] = __ldg(pq + 4 * k); qb[k] = __ldg(pq + 8 * R + 4 * k); }
    float o[24][4], m[2] = {-INFINITY, -INFINITY}, l[2] = {0.f, 0.f};
#pragma unroll
    for (int i = 0; i < 24; i++) o[i][0] = o[i][1] = o[i][2] = o[i][3] = 0.f;
#pragma unroll 1
    for (int key0 = 0; key0 < SK; key0 += 16) {
        float s[2][4];
#pragma unroll
        for (int j = 0; j < 2; j++) {
            s[j][0] = s[j][1] = s[j][2] = s[j][3] = 0.f;
            const uint4* pk = gk + ((size_t)head * SK + key0 + 8 * j + g) * R + c;
#pragma unroll
            for (int k = 0; k < 6; k++) {
                const uint4 x = __ldg(pk + 4 * k);
                mma_16816(s[j], qa[k].x, qb[k].x, qa[k].y, qb[k].y, x.x, x.y);
                mma_16816(s[j], qa[k].z, qb[k].z, qa[k].w, qb[k].w, x.z, x.w);
            }
        }
#pragma unroll
        for (int h = 0; h < 2; h++) {
            float f = fmaxf(fmaxf(s[0][2 * h], s[0][2 * h + 1]), fmaxf(s[1][2 * h], s[1][2 * h + 1]));
            f = fmaxf(f, __shfl_xor_sync(0xffffffffu, f, 1));
            f = fmaxf(f, __shfl_xor_sync(0xffffffffu, f, 2));
            f = fmaxf(f, m[h]);
            const float ref = f == -INFINITY ? 0.f : f;
            const float sc = ex2((m[h] - ref) * SCALE_LOG2E);
            m[h] = f;
            l[h] *= sc;
#pragma unroll
            for (int j = 0; j < 2; j++)
#pragma unroll
                for (int e = 0; e < 2; e++) { s[j][2 * h + e] = ex2((s[j][2 * h + e] - ref) * SCALE_LOG2E); l[h] += s[j][2 * h + e]; }
#pragma unroll
            for (int i = 0; i < 24; i++) { o[i][2 * h] *= sc; o[i][2 * h + 1] *= sc; }
        }
        const uint32_t a0 = pack_bf16(s[0][0], s[0][1]), a1 = pack_bf16(s[0][2], s[0][3]), a2 = pack_bf16(s[1][0], s[1][1]), a3 = pack_bf16(s[1][2], s[1][3]);
        const uint4* pv = gv + ((size_t)head * SK + key0 + 2 * c) * R + g;
#pragma unroll
        for (int sl = 0; sl < 3; sl++) {
            const uint4 v0 = __ldg(pv + 8 * sl), v1 = __ldg(pv + R + 8 * sl), v2 = __ldg(pv + 8 * R + 8 * sl), v3 = __ldg(pv + 9 * R + 8 * sl);
            const uint32_t w0[4] = {v0.x, v0.y, v0.z, v0.w}, w1[4] = {v1.x, v1.y, v1.z, v1.w}, w2[4] = {v2.x, v2.y, v2.z, v2.w}, w3[4] = {v3.x, v3.y, v3.z, v3.w};
#pragma unroll
            for (int i = 0; i < 8; i++)
                mma_16816(o[8 * sl + i], a0, a1, a2, a3, __byte_perm(w0[i >> 1], w1[i >> 1], (i & 1) ? 0x7632 : 0x5410),
                          __byte_perm(w2[i >> 1], w3[i >> 1], (i & 1) ? 0x7632 : 0x5410));
        }
    }
#pragma unroll
    for (int h = 0; h < 2; h++) {
        l[h] += __shfl_xor_sync(0xffffffffu, l[h], 1);
        l[h] += __shfl_xor_sync(0xffffffffu, l[h], 2);
        const float inv = 1.0f / l[h];
        uint4* po = go + ((size_t)head * SQ + row0 + 8 * h + g) * R + 2 * c;
#pragma unroll
        for (int sl = 0; sl < 3; sl++)
#pragma unroll
            for (int e = 0; e < 2; e++) {
                uint32_t w[4];
#pragma unroll
                for (int i = 0; i < 4; i++) w[i] = pack_bf16(o[8 * sl + 2 * i][2 * h + e] * inv, o[8 * sl + 2 * i + 1][2 * h + e] * inv);
                po[8 * sl + e] = make_uint4(w[0], w[1], w[2], w[3]);
            }
    }
}

#define ROLE_SETUP()                                                                          \
    uint32_t bid_;                                                                            \
    asm volatile("mov.u32 %0, %%ctaid.x;" : "=r"(bid_));                                      \
    bid_ += block0;                                                                           \
    const uint32_t rank = bid_ & 1;                                                           \
    const int cluster_id = bid_ >> 1;                                                         \
    const uint16_t* sched = SCHED[cluster_id];

__device__ __forceinline__ void consumer(const uint32_t sbase, const int warp_idx, const int lane, const uint32_t zero, const uint32_t block0, const uint4* __restrict__ gq,
                                         const uint4* __restrict__ gk, const uint4* __restrict__ gv, uint4* __restrict__ go) {
    ROLE_SETUP()
    const int wg = (warp_idx >> 2) - 1;
    const int tw = threadIdx.x & 127;
    const int bar_me = __shfl_sync(0xffffffffu, 1 + wg + (lane & zero), lane), bar_other = __shfl_sync(0xffffffffu, 2 - wg + (lane & zero), lane);
    const uint32_t qo = sbase + SM_QO + wg * BLK_BYTES + (warp_idx & 3) * 2 * GRP_BYTES;
    uint32_t q_lane[4];
#pragma unroll
    for (int i = 0; i < 4; i++)
        q_lane[i] = __shfl_sync(0xffffffffu, (qo + (lane & 7) * 128 + ((lane >> 3) & 1) * GRP_BYTES + (((lane >> 4) ^ (lane & 7)) << 4)) ^ (i * 32), lane);
    const uint32_t qfull = sbase + BAR_QFULL + 8 * wg, oready = sbase + BAR_OREADY + 8 * wg;

    float o[96], s[32], l[2];
    uint32_t q[48], p[16];
    uint32_t redo = 0;
    uint32_t v = V_DESC0;
    const uint32_t rel_pred = (tw | 96) == 96;
    const uint32_t rel_base = __shfl_sync(0xffffffffu, mapa(sbase, warp_idx & 2 ? cluster_rank() : warp_idx & 1) + BAR_DONE, 0);
    auto release = [&](int e) { mbar_arrive_cluster_pred(rel_base + 8 * (e & 3), rel_pred); };

    if (wg == 1) bar_arrive(1, 256);

    mbar_wait(qfull, 0);
    load_q_slab<0>(q, q_lane); load_q_slab<1>(q, q_lane); load_q_slab<2>(q, q_lane);
    scale_q<0, 48>(q);
    wait_blocks(sbase, 0);
    bar_sync(bar_me, 256);
    issue_qk<false>(s, q, 0);
    bar_arrive(bar_other, 256);
    const int n_items = sched[SCHED_COUNT];
    const uint32_t breaks = __shfl_sync(0xffffffffu, reinterpret_cast<const uint32_t*>(sched + SCHED_BREAKS)[wg], 0);
    wgmma_wait<0>();
    fence_regs(s);
    release(0);
    exp_sum<true>(s, l);
    pack_p(s, p);
    wait_blocks(sbase, 1);
    wait_blocks(sbase, 2);
    float inv[2][2] = {{0.f, 0.f}, {0.f, 0.f}};
    forget(o);

    auto phase_tail = [&](int b) {
        exp_sum<false>(s, l);
        fence_regs(s);
        mbar_wait(sbase + BAR_DUMMY, 1);
        wgmma_wait<0>();
        fence_regs(o);
        fence_regs(p);
        release(b + 1);
        pack_p(s, p);
    };

    for (int t = 0;; t++) {
        const bool has_next = t + 1 < n_items, chain = !(breaks >> t & 2);
        bar_sync(bar_me, 256);
        uint32_t keep = zero;
        issue_qk_stage<STAGE_SPLIT>(s, q, 1, o, inv, q_lane, keep);
        issue_pv<true, false>(o, p, sbase, 0, v);
        bar_arrive(bar_other, 256);
        wgmma_wait<1>();
        fence_regs(s);
        phase_tail(0);
        redo |= keep & p[15];
#pragma unroll 1
        for (int b = 1; b < NBLK - 2; b++) {
            bar_sync(bar_me, 256);
            issue_qk<false>(s, q, b + 1);
            if (b == PUB_B) publish_output(oready, lane);
            issue_pv<false>(o, p, sbase, b, v);
            bar_arrive(bar_other, 256);
            wgmma_wait<1>();
            fence_regs(s);
            phase_tail(b);
        }
        uint32_t c[8];
        mbar_wait(qfull, ~t & 1);
        bar_sync(bar_me, 256);
        issue_qk<true>(s, q, 7);
        wait_blocks(sbase, 8);
        wgmma_wait<2>();
        load_q_slab<0>(q, q_lane);
        issue_pv<false, false>(o, p, sbase, 6, v);
        bar_arrive(bar_other, 256);
        c[0] = sched_fence();
        wgmma_wait<2>();
        scale_q<0, 16, 4>(q);
        fence_regs(q);
        c[1] = sched_fence();
        load_q_slab<1>(q, q_lane);
        c[2] = sched_fence();
        wgmma_wait<1>();
        fence_regs(s);
        exp_only<0, P6N>(s);
        scale_q<1, 16, 4>(q); scale_q<2, 16, 4>(q); scale_q<3, 16, 4>(q);
        fence_regs(s); fence_regs(q);
        c[3] = sched_fence();
        scale_q<16, 32, 4>(q);
        fence_regs(q);
        c[4] = sched_fence();
        load_q_slab<2>(q, q_lane);
        c[5] = sched_fence();
        uint32_t p7[16];
        exp_only<P6N, 32>(s);
        scale_q<17, 32, 4>(q); scale_q<18, 32, 4>(q); scale_q<19, 32, 4>(q);
        fence_regs(s); fence_regs(q); fence_regs(l);
        c[6] = sched_fence();
        wgmma_wait<0>();
        fence_regs(o);
        fence_regs(p);
        release(7);
        sum_only(s, l);
        pack_p(s, p7);
        fence_regs(p7);
        c[7] = sched_fence();
        scale_q<32, 48>(q);
        redo |= c[0] & c[1] & c[2] & c[3] & c[4] & c[5] & c[6] & c[7] & zero;
        if (chain) {
            bar_sync(bar_me, 256);
            issue_qk<false>(s, q, 0);
            issue_pv<false>(o, p7, sbase, 7, v);
            bar_arrive(bar_other, 256);
            wgmma_wait<1>();
            fence_regs(s);
            row_normalisers(after(l[0], s[30], zero), after(l[1], s[31], zero), inv, redo, 1u << t, zero);
            exp_sum<true>(s, l);
            pack_p(s, p);
            fence_regs(p);
            fence_regs(s); fence_regs(l);
            wait_blocks(sbase, 10);
            wgmma_wait<0>();
            fence_regs(o);
            fence_regs(p7);
            release(8);
            stage_output<0, STAGE_SPLIT, true>(o, inv, q_lane);
            continue;
        }
        if (!has_next) {
            bar_sync(bar_me, 256);
            issue_pv<false>(o, p7, sbase, 7, v);
            if ((int)breaks < 0) bar_arrive(bar_other, 256);
            row_normalisers(l[0], l[1], inv, redo, 1u << t, zero);
            wgmma_wait<0>();
            fence_regs(o);
            stage_output<0, 12, true>(o, inv, q_lane);
            break;
        }
        float rs[8], rs0[8];
        bar_sync(bar_me, 256);
        fence_regs(o); fence_regs(p7);
        wgmma_fence();
        issue_rem_qk(rs0, 0);
        issue_pv<false, false, false>(o, p7, sbase, 7, v);
        issue_rem_qk(rs, 1);
        bar_arrive(bar_other, 256);
        const uint32_t t_lane = sbase + (lane & 7) * 128 + ((((warp_idx & 3) * 2 + (lane >> 3 & 1)) ^ (lane & 7)) << 4);
        const uint32_t pt_lane = t_lane + SM_PT + (lane >> 4) * 1024;
        float ro[3][8], rl[4] = {0.f, 0.f, 0.f, 0.f};
        bb_boundary(zero, l[0], l[1]);
        row_normalisers(l[0], l[1], inv, redo, 1u << t, zero);
        t++;
        bb_boundary(zero, inv);
        wgmma_wait<1>();
        fence_regs(rs0); fence_regs(o);
        release(0);
        rem_softmax(rs0, rl);
        rem_store(rs0, pt_lane);
        bb_boundary(zero, rl);
        wgmma_wait<0>();
        fence_regs(rs);
        rem_softmax(rs, rl);
        rem_store(rs, pt_lane + 2048);
        fence_async_smem();
        mbar_arrive_pred(qfull, tw == 0);
#pragma unroll
        for (int i = 0; i < 8; i++) ro[0][i] = ro[1][i] = ro[2][i] = 0.f;
#pragma unroll 1
        for (int b = 0;; b++) {
            bar_sync(bar_me, 256);
            fence_regs(ro[0]); fence_regs(ro[1]); fence_regs(ro[2]);
            wgmma_fence();
            issue_rem_qk(rs, b + 2);
            issue_rem_pv(ro, b & 1, v);
            bar_arrive(bar_other, 256);
            wgmma_wait<1>();
            fence_regs(rs);
            rem_softmax(rs, rl);
            fence_regs(rs);
            bb_boundary(zero, rl[0], rl[1]);
            wgmma_wait<0>();
            fence_regs(ro[0]); fence_regs(ro[1]); fence_regs(ro[2]);
            release(b + 1);
            bar_sync(3, 128);
            rem_store(rs, pt_lane + (b & 1) * 2048);
            if (b == NBLK - 3) break;
            fence_async_smem();
            if (b == MS0) stage_output<0, STAGE_SPLIT / 4, false>(o, inv, q_lane);
            if (b == MS0 + 1) stage_output<STAGE_SPLIT / 4, STAGE_SPLIT / 2, false>(o, inv, q_lane);
            if (b == MS0 + 2) stage_output<STAGE_SPLIT / 2, STAGE_SPLIT * 3 / 4, false>(o, inv, q_lane);
            if (b == MS0 + 3) stage_output<STAGE_SPLIT * 3 / 4, STAGE_SPLIT, false>(o, inv, q_lane);
        }
        {
            const uint32_t h0 = pack_bf16(rl[0], rl[1]), h1 = pack_bf16(rl[2], rl[3]);
            stsm_x4_t(pt_lane + (SM_REM - SM_PT), h0, pack_bf16(rl[0] - __uint_as_float(h0 << 16), rl[1] - __uint_as_float(h0 & 0xffff0000u)),
                      h1, pack_bf16(rl[2] - __uint_as_float(h1 << 16), rl[3] - __uint_as_float(h1 & 0xffff0000u)));
        }
        fence_async_smem();
        uint32_t ones[4] = {0x3F803F80u, 0x3F803F80u, 0x3F803F80u, 0x3F803F80u};
        auto rem_last = [&]() {
            wgmma_commit();
            issue_rem_pv(ro, 0, v);
            wait_blocks(sbase, 9);
            fence_regs(ro[0]); fence_regs(ro[1]); fence_regs(ro[2]);
            wgmma_fence();
            issue_rem_pv(ro, 1, v);
            bar_arrive(bar_other, 256);
            wgmma_wait<2>();
            fence_regs(rs);
            mbar_arrive_pred(sbase + BAR_SUMS, lane == 0);
            if (sum_unsafe(rs[0]) | sum_unsafe(rs[1]) | sum_unsafe(rs[4]) | sum_unsafe(rs[5])) redo |= 1u << t;
#pragma unroll
            for (int i = 0; i < 4; i++) asm("rcp.approx.ftz.f32 %0, %1;" : "=f"(rl[i]) : "f"(rs[(i & 2) * 2 + (i & 1)]));
        };
        auto rem_stage = [&]() {
            mbar_wait(sbase + BAR_SUMS, wg ^ 1);
            wgmma_wait<0>();
            fence_regs(ro[0]); fence_regs(ro[1]); fence_regs(ro[2]);
            release(7);
            release(0);
#pragma unroll
            for (int m = 0; m < 3; m++)
                stsm_x4_t(t_lane + SM_REM + (lane >> 4) * GRP_BYTES + m * SLAB_BYTES, pack_bf16(ro[m][0] * rl[0], ro[m][1] * rl[1]), pack_bf16(ro[m][2] * rl[0], ro[m][3] * rl[1]),
                          pack_bf16(ro[m][4] * rl[2], ro[m][5] * rl[3]), pack_bf16(ro[m][6] * rl[2], ro[m][7] * rl[3]));
        };
        const uint64_t sum_desc = make_desc(((SM_BASE + SM_REM) >> 4) | (1u << 16), PT_DESC_HI);
        fence_regs(ones);
        bar_sync(bar_me, 256);
        fence_regs(ro[0]); fence_regs(ro[1]); fence_regs(ro[2]);
        if (t + 1 == n_items) {
            wgmma_fence();
            wgmma_rl_init(rs, ones[0], ones[1], ones[2], ones[3], sum_desc);
#pragma unroll
            for (int k = 1; k < 4; k++) wgmma_rl(rs, ones[0], ones[1], ones[2], ones[3], sum_desc + 2 * k);
            rem_last();
            stage_output<STAGE_SPLIT, 12, false>(o, inv, q_lane);
            rem_stage();
            break;
        }
        fence_regs(q);
        wgmma_fence();
        {
            uint64_t desc = k_desc(0);
#pragma unroll
            for (int k = 0; k < 12; k++) {
                if (k == 0) wgmma_qk_init(s, q[0], q[1], q[2], q[3], desc);
                else wgmma_qk(s, q[4 * k], q[4 * k + 1], q[4 * k + 2], q[4 * k + 3], desc);
                if (k < 11) desc += k_step(k);
                if (k == SK0) wgmma_rl_init(rs, ones[0], ones[1], ones[2], ones[3], sum_desc);
#pragma unroll
                for (int j = 1; j < 4; j++)
                    if (k == SK0 + j * SDK) wgmma_rl(rs, ones[0], ones[1], ones[2], ones[3], sum_desc + 2 * j);
            }
        }
        rem_last();
        fence_regs(s);
        exp_sum<true>(s, l);
        pack_p(s, p);
        rem_stage();
        wait_blocks(sbase, 2);
    }
    redo = __reduce_or_sync(0xffffffffu, redo);
    if (redo) asm volatile("st.shared.u32 [%0], %1;" ::"r"(sbase + SM_REDO + 4 * wg), "r"(1) : "memory");
    publish_output(oready, lane);
    if (redo) {
        mbar_wait(sbase + BAR_STORED + 8 * wg, 0);
        asm volatile("fence.proxy.async;" ::: "memory");
        for (; redo; redo &= redo - 1) {
            const Item it = decode_item(sched[__ffs(redo) - 1], rank, wg);
            const int row0 = it.grp * 8 + (warp_idx & 3) * 16;
            if (row0 < SQ) exact_rows(gq, gk, gv, go, it.head, row0, lane);
        }
    }
}

__global__ void __cluster_dims__() __launch_bounds__(384, 1)
attn_fwd_kernel(const __grid_constant__ CUtensorMap tmQ, const __grid_constant__ CUtensorMap tmK, const __grid_constant__ CUtensorMap tmV,
                const __grid_constant__ CUtensorMap tmO, const __grid_constant__ CUtensorMap tmR, const uint32_t zero, const uint32_t block0,
                const __grid_constant__ Starts starts,
                const uint4* __restrict__ gq, const uint4* __restrict__ gk, const uint4* __restrict__ gv, uint4* __restrict__ go) {
    extern __shared__ __align__(1024) uint8_t smem_raw[];
    const uint32_t sbase = smem_u32(smem_raw);
    const int warp_idx = __shfl_sync(0xffffffffu, threadIdx.x >> 5, 0);
    const int lane = threadIdx.x & 31;
    asm volatile("griddepcontrol.launch_dependents;");

    if (threadIdx.x == 0) {
        if ((sbase & 0x3FFFF) != SM_BASE) __trap();
        const uint32_t done = cluster_rank() < 2 ? 2 * cluster_size() + 4 : 4;
        for (int i = 0; i < 4; i++) { mbar_init(sbase + BAR_FULL + 8 * i, 1); mbar_init(sbase + BAR_DONE + 8 * i, done); }
        for (int i = 0; i < 2; i++) { mbar_init(sbase + BAR_QFULL + 8 * i, 1); mbar_init(sbase + BAR_OREADY + 8 * i, 4); mbar_init(sbase + BAR_STORED + 8 * i, 1); }
        mbar_init(sbase + BAR_DUMMY, 1);
        mbar_init(sbase + BAR_REMFREE, 1);
        mbar_init(sbase + BAR_SUMS, 4);
        asm volatile("st.shared.v2.u32 [%0], {%1, %1};" ::"r"(sbase + SM_REDO), "r"(0) : "memory");
        asm volatile("fence.mbarrier_init.release.cluster;" ::: "memory");
    } else if (threadIdx.x == 32) {
        asm volatile("prefetch.tensormap [%0];" ::"l"(&tmQ) : "memory");
        asm volatile("prefetch.tensormap [%0];" ::"l"(&tmK) : "memory");
        asm volatile("prefetch.tensormap [%0];" ::"l"(&tmV) : "memory");
        asm volatile("prefetch.tensormap [%0];" ::"l"(&tmO) : "memory");
        asm volatile("prefetch.tensormap [%0];" ::"l"(&tmR) : "memory");
    }
    __syncthreads();
    asm volatile("barrier.cluster.arrive.relaxed.aligned;" ::: "memory");
    const uint32_t start = starts.of[blockIdx.x >> 1];
    if (warp_idx < 3 && start == 0) {
        if (elect_one()) {
            const int w = warp_idx - 1;
            const Item q = decode_item(first_entry(blockIdx.x + block0 >> 1), blockIdx.x & 1, w);
            if (warp_idx == 0) {
                mbar_expect_tx(sbase + BAR_FULL, BLK_BYTES);
                tma_load_kv(sbase + k_addr(0), &tmK, q.head * (SK / 8), sbase + BAR_FULL);
            } else {
                mbar_expect_tx(sbase + BAR_QFULL + 8 * w, BLK_BYTES);
                tma_load_q(sbase + SM_QO + w * BLK_BYTES, &tmQ, q.grp, q.head, sbase + BAR_QFULL + 8 * w);
            }
        }
        __syncwarp();
    }
    asm volatile("barrier.cluster.wait.aligned;" ::: "memory");

    if (warp_idx < 4) {
        asm volatile("setmaxnreg.dec.sync.aligned.u32 %0;" ::"n"(PRODUCER_REGS));
        ROLE_SETUP()
        for (const uint32_t t1 = clock() + start * 16; (int)(clock() - t1) < 0;) __nanosleep(20);
        if (warp_idx == 0) {
            if (elect_one()) {
                const uint32_t crank = cluster_rank();
                const uint16_t all = (1u << cluster_size()) - 1;
                auto load = [&](const CUtensorMap* tm, uint32_t owner, const Item& it, int blk, uint32_t dst, uint32_t full) {
                    const int grp = it.head * (SK / 8) + blk * 8;
                    if (!it.mc) tma_load_kv(sbase + dst, tm, grp, full);
                    else if (crank == owner) tma_load_kv_mc(sbase + dst, tm, grp, full, all);
                };
                Item iv = decode_item(first_entry(cluster_id), rank, 0), ik = iv;
                for (int e = start == 0; e < 2; e++) {
                    mbar_expect_tx(sbase + BAR_FULL + 8 * e, BLK_BYTES);
                    load(&tmK, 0, ik, e, k_addr(e), sbase + BAR_FULL + 8 * e);
                }
                uint32_t v = SM_V;
                bool more = true;
                for (int t = 1; more; t++) {
#pragma unroll 1
                    for (int e = 2; e < NBLK + 2; e++) {
                        if (e == NBLK) { more = t < sched[SCHED_COUNT]; ik = decode_item(sched[t], rank, 0); }
                        const uint32_t full = sbase + BAR_FULL + 8 * (e & 3);
                        mbar_sleep(full + (BAR_DONE - BAR_FULL), ~e >> 2 & 1);
                        mbar_expect_tx(full, more ? 2 * BLK_BYTES : BLK_BYTES);
                        load(&tmV, 1, iv, e - 2, v, full);
                        if (more) load(&tmK, 0, ik, e & 7, k_addr(e), full);
                        next_v(v);
                    }
                    iv = ik;
                }
            }
        } else if (warp_idx < 3) {
            if (elect_one()) {
                const int w = warp_idx - 1;
                const uint32_t buf = sbase + SM_QO + w * BLK_BYTES;
                const uint32_t qfull = sbase + BAR_QFULL + 8 * w, oready = sbase + BAR_OREADY + 8 * w;
                if (start) {
                    const Item q = decode_item(first_entry(cluster_id), rank, w);
                    mbar_expect_tx(qfull, BLK_BYTES);
                    tma_load_q(buf, &tmQ, q.grp, q.head, qfull);
                }
                const int n_items = sched[SCHED_COUNT];
                uint32_t t0 = 0;
                for (int r = 0, phase = 0; r <= n_items; r++, phase ^= 1) {
                    uint32_t d = sched[r] >> 11;
                    if (d >= 16) {
                        const Item ro = decode_item(sched[r - 1], rank, w);
                        for (t0 += (d >> 2) * 1536 + (ro.mc ? 0 : ro.rem ? 10200 : -2100); (int)(clock() - t0) < 0;) __nanosleep(200);
                        const int x = r + 1 + decode_item(sched[r + 1], rank, w).rem;
                        const Item q = decode_item(sched[x], rank, w);
                        if (x < n_items) tma_prefetch_q(&tmQ, q.grp, q.head);
                        d = (d & 3) * 7;
                    }
                    mbar_sleep(oready, phase);
                    t0 = clock();
                    for (d <<= r ? 7 : 8; (uint32_t)clock() - t0 < d;) __nanosleep(50);
                    if (r > 0) {
                        const Item ro = decode_item(sched[r - 1], rank, w), o = decode_item(sched[r - 1 - ro.rem], rank, w);
                        tma_store_o(&tmO, buf, o.grp, o.head);
                        if (ro.rem) tma_store_o(&tmO, sbase + SM_REM, ro.grp, ro.head);
                        bulk_commit();
                        bulk_wait_read();
                        if (ro.rem) mbar_arrive(sbase + BAR_REMFREE);
                    }
                    if (r < n_items) {
                        const Item rq = decode_item(sched[r + 1], rank, w), q = decode_item(sched[r + 1 + rq.rem], rank, w);
                        const bool full = r + 1 + rq.rem < n_items;
                        mbar_expect_tx(qfull, (rq.rem ? REM_BYTES : 0) + (full ? BLK_BYTES : 0));
                        if (full) tma_load_q(buf, &tmQ, q.grp, q.head, qfull);
                        if (rq.rem) {
                            mbar_sleep(sbase + BAR_REMFREE, w);
                            tma_load_q(sbase + SM_REM, &tmR, rq.grp, rq.head, qfull);
                        }
                        r += rq.rem;
                    }
                }
                uint32_t redo;
                asm volatile("ld.shared.u32 %0, [%1];" : "=r"(redo) : "r"(sbase + SM_REDO + 4 * w) : "memory");
                if (redo) {
                    asm volatile("cp.async.bulk.wait_group 0;\nfence.proxy.async;" ::: "memory");
                    mbar_arrive(sbase + BAR_STORED + 8 * w);
                }
            }
        }
        else if (T_KVPF && elect_one()) {
            const int n_items = sched[SCHED_COUNT];
            const char* kv = reinterpret_cast<const char*>(rank ? gv : gk);
#pragma unroll 1
            for (int e = 4; e < NBLK * n_items; e++) {
                mbar_sleep(sbase + BAR_DONE + 8 * (e & 3), ~e >> 2 & 1);
                const int x = e + T_KVPF - 2 * rank;
                const uint32_t it = sched[x >> 3] & 0x7FF;
                if (x >> 3 < n_items && (it & 3) != 3)
                    asm volatile("cp.async.bulk.prefetch.L2.global [%0], %1;" ::"l"(kv + ((it >> 2) * 24 + (x & 7) * 3 + (it & 3)) * (BLK_BYTES / 3)), "r"(BLK_BYTES / 3) : "memory");
            }
        }
    } else {
        asm volatile("setmaxnreg.inc.sync.aligned.u32 %0;" ::"n"(CONSUMER_REGS));
        consumer(sbase, warp_idx, lane, zero, block0, gq, gk, gv, go);
    }
    asm volatile("barrier.cluster.arrive.relaxed.aligned;\nbarrier.cluster.wait.aligned;" ::: "memory");
}

typedef CUresult (*EncodeTiledFn)(CUtensorMap*, CUtensorMapDataType, cuuint32_t, void*, const cuuint64_t*, const cuuint64_t*,
                                  const cuuint32_t*, const cuuint32_t*, CUtensorMapInterleave, CUtensorMapSwizzle,
                                  CUtensorMapL2promotion, CUtensorMapFloatOOBfill);

}

extern "C" void kernel_launch(void* const* d_in, const int* in_sizes, int n_in, void* d_out, int out_size) {
    (void)in_sizes; (void)n_in; (void)out_size;
    static CUtensorMap tmQ, tmK, tmV, tmO, tmR;
    static void* cached[4] = {nullptr, nullptr, nullptr, nullptr};
    static int big = 0;
    cudaLaunchAttribute attr[2];
    attr[0].id = cudaLaunchAttributeClusterDimension;
    attr[0].val.clusterDim.x = 6; attr[0].val.clusterDim.y = 1; attr[0].val.clusterDim.z = 1;
    attr[1].id = cudaLaunchAttributeProgrammaticStreamSerialization;
    attr[1].val.programmaticStreamSerializationAllowed = 1;
    cudaLaunchConfig_t cfg = {};
    cfg.gridDim = 6 * BIG_CLUSTERS; cfg.blockDim = 384; cfg.dynamicSmemBytes = SMEM_BYTES; cfg.stream = cudaStreamPerThread;
    cfg.attrs = attr; cfg.numAttrs = 1;
    if (cached[0] != d_in[0] || cached[1] != d_in[1] || cached[2] != d_in[2] || cached[3] != d_out) {
        void* fn = nullptr;
        cudaDriverEntryPointQueryResult qr;
        cudaGetDriverEntryPoint("cuTensorMapEncodeTiled", &fn, cudaEnableDefault, &qr);
        EncodeTiledFn enc = (EncodeTiledFn)fn;
        const cuuint32_t es[5] = {1, 1, 1, 1, 1};
        const cuuint32_t box[5] = {64, 8, 3, 8, 1};
        const cuuint32_t box_rem[5] = {64, 8, 3, 2, 1};
        {
            cuuint64_t gd[5] = {64, 8, 3, SQ / 8, NHEADS};
            cuuint64_t gs[4] = {ROW_BYTES, 128, 8 * ROW_BYTES, (cuuint64_t)SQ * ROW_BYTES};
            enc(&tmQ, CU_TENSOR_MAP_DATA_TYPE_BFLOAT16, 5, d_in[0], gd, gs, box, es, CU_TENSOR_MAP_INTERLEAVE_NONE,
                CU_TENSOR_MAP_SWIZZLE_128B, CU_TENSOR_MAP_L2_PROMOTION_NONE, CU_TENSOR_MAP_FLOAT_OOB_FILL_NONE);
            enc(&tmR, CU_TENSOR_MAP_DATA_TYPE_BFLOAT16, 5, d_in[0], gd, gs, box_rem, es, CU_TENSOR_MAP_INTERLEAVE_NONE,
                CU_TENSOR_MAP_SWIZZLE_128B, CU_TENSOR_MAP_L2_PROMOTION_NONE, CU_TENSOR_MAP_FLOAT_OOB_FILL_NONE);
            enc(&tmO, CU_TENSOR_MAP_DATA_TYPE_BFLOAT16, 5, d_out, gd, gs, box, es, CU_TENSOR_MAP_INTERLEAVE_NONE,
                CU_TENSOR_MAP_SWIZZLE_128B, CU_TENSOR_MAP_L2_PROMOTION_NONE, CU_TENSOR_MAP_FLOAT_OOB_FILL_NONE);
        }
        {
            cuuint64_t gd[4] = {64, 8, 3, (cuuint64_t)NHEADS * SK / 8};
            cuuint64_t gs[3] = {ROW_BYTES, 128, 8 * ROW_BYTES};
            enc(&tmK, CU_TENSOR_MAP_DATA_TYPE_BFLOAT16, 4, d_in[1], gd, gs, box, es, CU_TENSOR_MAP_INTERLEAVE_NONE,
                CU_TENSOR_MAP_SWIZZLE_128B, CU_TENSOR_MAP_L2_PROMOTION_NONE, CU_TENSOR_MAP_FLOAT_OOB_FILL_NONE);
            enc(&tmV, CU_TENSOR_MAP_DATA_TYPE_BFLOAT16, 4, d_in[2], gd, gs, box, es, CU_TENSOR_MAP_INTERLEAVE_NONE,
                CU_TENSOR_MAP_SWIZZLE_128B, CU_TENSOR_MAP_L2_PROMOTION_NONE, CU_TENSOR_MAP_FLOAT_OOB_FILL_NONE);
        }
        cudaFuncSetAttribute(attn_fwd_kernel, cudaFuncAttributeMaxDynamicSharedMemorySize, SMEM_BYTES);
        if (cudaOccupancyMaxActiveClusters(&big, attn_fwd_kernel, &cfg) != cudaSuccess) { big = 0; cudaGetLastError(); }
        cached[0] = d_in[0]; cached[1] = d_in[1]; cached[2] = d_in[2]; cached[3] = d_out;
    }
    auto launch = [&](uint32_t block0, uint32_t blocks, uint32_t cluster) {
        Starts starts = {};
        for (uint32_t i = 0; i < blocks / 2; i++) starts.of[i] = START_TIME[block0 / 2 + i];
        cfg.gridDim = blocks;
        cfg.numAttrs = block0 ? 2 : 1;
        attr[0].val.clusterDim.x = cluster;
        cudaLaunchKernelEx(&cfg, attn_fwd_kernel, tmQ, tmK, tmV, tmO, tmR, 0u, block0, starts, (const uint4*)d_in[0], (const uint4*)d_in[1],
                           (const uint4*)d_in[2], (uint4*)d_out);
    };
    launch(0, 6 * BIG_CLUSTERS, big >= BIG_CLUSTERS ? 6 : 2);
    launch(6 * BIG_CLUSTERS, 2 * NUM_CLUSTERS - 6 * BIG_CLUSTERS, 2);
}
```
